```python
import torch

def _softmax(x, axis=-1):
    return torch.softmax(x, dim=axis)
def _gelu(x):
    return torch.nn.functional.gelu(x, approximate="tanh")
def _silu(x):
    return torch.nn.functional.silu(x)
def _sigmoid(x):
    return torch.sigmoid(x)
def _layernorm(x, axis=-1, eps=1e-5):
    m = x.mean(dim=axis, keepdim=True)
    v = x.var(dim=axis, keepdim=True, unbiased=False)
    return (x - m) / torch.sqrt(v + eps)
def _scatter_add(tgt, idx, src, axis=0):
    return tgt.clone().index_add_(axis, idx, src)
def _segment_sum(src, seg, n):
    out = torch.zeros((n,) + src.shape[1:], dtype=src.dtype)
    return out.index_add_(0, seg, src)
def _pad(x, pw):
    flat = tuple(v for pair in reversed(pw) for v in pair)
    return torch.nn.functional.pad(x, flat)

kernel_name = 'gated_mix__sliding_local_dilated__mha_block__prompt'

def setup_inputs():

    _w = (lambda a: (lambda t: t.to(torch.bfloat16) if t.is_floating_point() else t)(torch.as_tensor(a)))
    def _A_setup():
        B, S, D = 1, 2048, 640
        return {
            "x": _w((lambda *s: torch.randn(*s, dtype=torch.bfloat16) * 0.05)(B, S, D)),
            "wqkv": _w((lambda *s: torch.randn(*s, dtype=torch.bfloat16) * 1.6)(D, 3 * D)),
            "wo": _w((lambda *s: torch.randn(*s, dtype=torch.bfloat16) * 0.05)(D, D)),
        }
    _A_in = _A_setup()

    def _B_setup():
        B, S, D, H = 1, 2048, 640, 32
        return {
            "x": _w((lambda *s: torch.randn(*s, dtype=torch.bfloat16) * 0.05)(B, S, D)),
            "wqkv": _w((lambda *s: torch.randn(*s, dtype=torch.bfloat16) * 1.6)(D, 3 * D)),
            "wo": _w((lambda *s: torch.randn(*s, dtype=torch.bfloat16) * 0.1)(D, D)),
        }
    _B_in = _B_setup()

    return {
        "A_x": _A_in["x"],
        "A_wqkv": _A_in["wqkv"],
        "A_wo": _A_in["wo"],
        "B_x": _B_in["x"],
        "B_wqkv": _B_in["wqkv"],
        "B_wo": _B_in["wo"],
        "gate_w": _w((lambda *s: torch.randn(*s, dtype=torch.bfloat16) * 0.05)(640) * 16.0),
    }

def reference(A_x, A_wqkv, A_wo, B_x, B_wqkv, B_wo, gate_w):
    def _A_ref(x, wqkv, wo):
        B, S, D = x.shape
        H = 32; Dh = D // H
        W, dil = 8, 2
        qkv = (lambda x, *d: x.permute(*d))((x @ wqkv).reshape(B, S, 3, H, Dh), 2, 0, 3, 1, 4)
        q, k, v = qkv[0], qkv[1], qkv[2]
        scale = Dh ** -0.5
        pos = torch.arange(S)
        off = torch.arange(W) * dil
        idx = pos[:, None] - off[None, :]
        mask = idx >= 0
        idx_c = torch.where(mask, idx, 0).reshape(-1)
        kg = k[:, :, idx_c, :].reshape(B, H, S, W, Dh)
        vg = v[:, :, idx_c, :].reshape(B, H, S, W, Dh)
        logits = torch.einsum("bhsd,bhswd->bhsw", q, kg) * scale
        logits = torch.where(mask[None, None, :, :], logits, -1e9)
        attn = _softmax(logits, axis=-1)
        o = torch.einsum("bhsw,bhswd->bhsd", attn, vg)
        return (lambda x, *d: x.permute(*d))(o, 0, 2, 1, 3).reshape(B, S, D) @ wo

    def _B_ref(x, wqkv, wo):
        B, S, D = x.shape
        H = 32
        Dh = D // H
        qkv = (lambda x, *d: x.permute(*d))((x @ wqkv).reshape(B, S, 3, H, Dh), 2, 0, 3, 1, 4)
        q, k, v = qkv[0], qkv[1], qkv[2]
        scores = torch.einsum("bhqd,bhkd->bhqk", q, k) * (Dh ** -0.5)
        p = _softmax(scores, axis=-1)
        o = torch.einsum("bhqk,bhkd->bhqd", p, v)
        return (lambda x, *d: x.permute(*d))(o, 0, 2, 1, 3).reshape(B, S, D) @ wo

    x = A_x
    g = _sigmoid((x * gate_w).sum(-1, keepdims=True))
    a = _A_ref(x, A_wqkv, A_wo)
    b = _B_ref(x, B_wqkv, B_wo)
    return g * a + (1 - g) * b
```

```cpp
#include <cuda_runtime.h>
#include <cuda_bf16.h>
#include <cuda.h>
#include <stdint.h>

namespace {

constexpr int SEQ = 2048, DM = 640;
constexpr int HEAD_BYTES = 256 * 384;
constexpr uint32_t POLY16 = 0xb5bbu;
constexpr float QSCALE = 0.22360679774997896f * 1.4426950408889634f;

__device__ __align__(1024) uint8_t g_qkv[2 * 96 * HEAD_BYTES];
__device__ float g_gate[SEQ];
__device__ __align__(1024) __nv_bfloat16 g_att[SEQ * 1280];

__device__ __forceinline__ uint32_t smem_u32(const void* p) { return (uint32_t)__cvta_generic_to_shared(p); }
__device__ __forceinline__ void mbar_init(uint32_t bar, int cnt) { asm volatile("mbarrier.init.shared::cta.b64 [%0], %1;" ::"r"(bar), "r"(cnt) : "memory"); }
__device__ __forceinline__ void mbar_expect_tx(uint32_t bar, int bytes) { asm volatile("mbarrier.arrive.expect_tx.shared::cta.b64 _, [%0], %1;" ::"r"(bar), "r"(bytes) : "memory"); }
__device__ __forceinline__ void mbar_arrive(uint32_t bar) { asm volatile("mbarrier.arrive.shared::cta.b64 _, [%0];" ::"r"(bar) : "memory"); }
__device__ __forceinline__ bool mbar_try(uint32_t bar, uint32_t parity) {
    uint32_t ok;
    asm volatile("{\n.reg .pred p;\nmbarrier.try_wait.parity.shared::cta.b64 p, [%1], %2;\nselp.u32 %0, 1, 0, p;\n}\n" : "=r"(ok) : "r"(bar), "r"(parity) : "memory");
    return ok;
}
__device__ __forceinline__ void mbar_wait(uint32_t bar, uint32_t parity) {
    if (mbar_try(bar, parity)) return;
#pragma unroll 1
    for (int i = 0; i < (1 << 21); i++)
        if (mbar_try(bar, parity)) return;
    __trap();
}
__device__ __forceinline__ void fence_mbar_init() { asm volatile("fence.mbarrier_init.release.cluster;" ::: "memory"); }
__device__ __forceinline__ void tma_2d(uint32_t dst, const CUtensorMap* tm, int c0, int c1, uint32_t bar) {
    asm volatile("cp.async.bulk.tensor.2d.shared::cluster.global.mbarrier::complete_tx::bytes [%0], [%1, {%2, %3}], [%4];"
                 ::"r"(dst), "l"(tm), "r"(c0), "r"(c1), "r"(bar) : "memory");
}
__device__ __forceinline__ void tma_3d(uint32_t dst, const CUtensorMap* tm, int c0, int c1, int c2, uint32_t bar) {
    asm volatile("cp.async.bulk.tensor.3d.shared::cluster.global.mbarrier::complete_tx::bytes [%0], [%1, {%2, %3, %4}], [%5];"
                 ::"r"(dst), "l"(tm), "r"(c0), "r"(c1), "r"(c2), "r"(bar) : "memory");
}
__device__ __forceinline__ void bulk_g2s(uint32_t dst, const void* src, int bytes, uint32_t bar) {
    asm volatile("cp.async.bulk.shared::cluster.global.mbarrier::complete_tx::bytes [%0], [%1], %2, [%3];"
                 ::"r"(dst), "l"(src), "r"(bytes), "r"(bar) : "memory");
}
__device__ __forceinline__ void prefetch_tmap(const CUtensorMap* tm) { asm volatile("prefetch.tensormap [%0];" ::"l"(tm) : "memory"); }
__device__ __forceinline__ void pdl_wait() { asm volatile("griddepcontrol.wait;" ::: "memory"); }
__device__ __forceinline__ void pdl_launch() { asm volatile("griddepcontrol.launch_dependents;" ::: "memory"); }
__device__ __forceinline__ void wg_fence() { asm volatile("wgmma.fence.sync.aligned;" ::: "memory"); }
__device__ __forceinline__ void wg_commit() { asm volatile("wgmma.commit_group.sync.aligned;" ::: "memory"); }
template <int N> __device__ __forceinline__ void wg_wait() { asm volatile("wgmma.wait_group.sync.aligned %0;" ::"n"(N) : "memory"); }
__device__ __forceinline__ uint64_t mkdesc(uint32_t addr, uint32_t lbo, uint32_t sbo, uint32_t swz) {
    return (uint64_t)((addr & 0x3FFFF) >> 4) | ((uint64_t)(lbo >> 4) << 16) | ((uint64_t)(sbo >> 4) << 32) | ((uint64_t)swz << 62);
}
template <int N> __device__ __forceinline__ void pin(float (&r)[N]) {
#pragma unroll
    for (int i = 0; i < N; i++) asm volatile("" : "+f"(r[i])::"memory");
}
template <int N> __device__ __forceinline__ void pin(uint32_t (&r)[N]) {
#pragma unroll
    for (int i = 0; i < N; i++) asm volatile("" : "+r"(r[i])::"memory");
}
__device__ __forceinline__ float ex2(float x) { float y; asm("ex2.approx.ftz.f32 %0, %1;" : "=f"(y) : "f"(x)); return y; }
__device__ __forceinline__ uint32_t pack2(float lo, float hi) { uint32_t r; asm("cvt.rn.bf16x2.f32 %0, %1, %2;" : "=r"(r) : "f"(hi), "f"(lo)); return r; }
__device__ __forceinline__ uint32_t hfma2(uint32_t a, uint32_t b, uint32_t c) { uint32_t d; asm("fma.rn.bf16x2 %0, %1, %2, %3;" : "=r"(d) : "r"(a), "r"(b), "r"(c)); return d; }
__device__ __forceinline__ float bf_lo(uint32_t v) { return __uint_as_float(v << 16); }
__device__ __forceinline__ float bf_hi(uint32_t v) { return __uint_as_float(v & 0xffff0000u); }
__device__ __forceinline__ void mma16816(float (&c)[4], uint32_t a0, uint32_t a1, uint32_t a2, uint32_t a3, uint32_t b0, uint32_t b1) {
    asm volatile("mma.sync.aligned.m16n8k16.row.col.f32.bf16.bf16.f32 {%0,%1,%2,%3}, {%4,%5,%6,%7}, {%8,%9}, {%0,%1,%2,%3};"
                 : "+f"(c[0]), "+f"(c[1]), "+f"(c[2]), "+f"(c[3]) : "r"(a0), "r"(a1), "r"(a2), "r"(a3), "r"(b0), "r"(b1));
}
__device__ __forceinline__ void mma1688(float (&c)[4], uint32_t a0, uint32_t a1, uint32_t b0) {
    asm volatile("mma.sync.aligned.m16n8k8.row.col.f32.bf16.bf16.f32 {%0,%1,%2,%3}, {%4,%5}, {%6}, {%0,%1,%2,%3};"
                 : "+f"(c[0]), "+f"(c[1]), "+f"(c[2]), "+f"(c[3]) : "r"(a0), "r"(a1), "r"(b0));
}
__device__ __forceinline__ uint32_t movm_t(uint32_t a) { uint32_t d; asm volatile("movmatrix.sync.aligned.m8n8.trans.b16 %0, %1;" : "=r"(d) : "r"(a)); return d; }
__device__ __forceinline__ uint32_t lds32(uint32_t a) { uint32_t v; asm volatile("ld.shared.b32 %0, [%1];" : "=r"(v) : "r"(a)); return v; }
__device__ __forceinline__ uint4 lds128(uint32_t a) { uint4 v; asm volatile("ld.shared.v4.b32 {%0,%1,%2,%3}, [%4];" : "=r"(v.x), "=r"(v.y), "=r"(v.z), "=r"(v.w) : "r"(a)); return v; }

__device__ __forceinline__ void wgmma_ss240(float (&d)[120], uint64_t da, uint64_t db, int sd) {
    asm volatile("{\n.reg .pred p;\nsetp.ne.b32 p, %122, 0;\n"
        "wgmma.mma_async.sync.aligned.m64n240k16.f32.bf16.bf16 "
        "{%0,%1,%2,%3,%4,%5,%6,%7,%8,%9,%10,%11,%12,%13,%14,%15,%16,%17,%18,%19,"
        "%20,%21,%22,%23,%24,%25,%26,%27,%28,%29,%30,%31,%32,%33,%34,%35,%36,%37,%38,%39,"
        "%40,%41,%42,%43,%44,%45,%46,%47,%48,%49,%50,%51,%52,%53,%54,%55,%56,%57,%58,%59,"
        "%60,%61,%62,%63,%64,%65,%66,%67,%68,%69,%70,%71,%72,%73,%74,%75,%76,%77,%78,%79,"
        "%80,%81,%82,%83,%84,%85,%86,%87,%88,%89,%90,%91,%92,%93,%94,%95,%96,%97,%98,%99,"
        "%100,%101,%102,%103,%104,%105,%106,%107,%108,%109,%110,%111,%112,%113,%114,%115,%116,%117,%118,%119}, "
        "%120, %121, p, 1, 1, 0, 1;\n}\n"
        : "+f"(d[0]), "+f"(d[1]), "+f"(d[2]), "+f"(d[3]), "+f"(d[4]), "+f"(d[5]), "+f"(d[6]), "+f"(d[7]), "+f"(d[8]), "+f"(d[9]),
          "+f"(d[10]), "+f"(d[11]), "+f"(d[12]), "+f"(d[13]), "+f"(d[14]), "+f"(d[15]), "+f"(d[16]), "+f"(d[17]), "+f"(d[18]), "+f"(d[19]),
          "+f"(d[20]), "+f"(d[21]), "+f"(d[22]), "+f"(d[23]), "+f"(d[24]), "+f"(d[25]), "+f"(d[26]), "+f"(d[27]), "+f"(d[28]), "+f"(d[29]),
          "+f"(d[30]), "+f"(d[31]), "+f"(d[32]), "+f"(d[33]), "+f"(d[34]), "+f"(d[35]), "+f"(d[36]), "+f"(d[37]), "+f"(d[38]), "+f"(d[39]),
          "+f"(d[40]), "+f"(d[41]), "+f"(d[42]), "+f"(d[43]), "+f"(d[44]), "+f"(d[45]), "+f"(d[46]), "+f"(d[47]), "+f"(d[48]), "+f"(d[49]),
          "+f"(d[50]), "+f"(d[51]), "+f"(d[52]), "+f"(d[53]), "+f"(d[54]), "+f"(d[55]), "+f"(d[56]), "+f"(d[57]), "+f"(d[58]), "+f"(d[59]),
          "+f"(d[60]), "+f"(d[61]), "+f"(d[62]), "+f"(d[63]), "+f"(d[64]), "+f"(d[65]), "+f"(d[66]), "+f"(d[67]), "+f"(d[68]), "+f"(d[69]),
          "+f"(d[70]), "+f"(d[71]), "+f"(d[72]), "+f"(d[73]), "+f"(d[74]), "+f"(d[75]), "+f"(d[76]), "+f"(d[77]), "+f"(d[78]), "+f"(d[79]),
          "+f"(d[80]), "+f"(d[81]), "+f"(d[82]), "+f"(d[83]), "+f"(d[84]), "+f"(d[85]), "+f"(d[86]), "+f"(d[87]), "+f"(d[88]), "+f"(d[89]),
          "+f"(d[90]), "+f"(d[91]), "+f"(d[92]), "+f"(d[93]), "+f"(d[94]), "+f"(d[95]), "+f"(d[96]), "+f"(d[97]), "+f"(d[98]), "+f"(d[99]),
          "+f"(d[100]), "+f"(d[101]), "+f"(d[102]), "+f"(d[103]), "+f"(d[104]), "+f"(d[105]), "+f"(d[106]), "+f"(d[107]), "+f"(d[108]), "+f"(d[109]),
          "+f"(d[110]), "+f"(d[111]), "+f"(d[112]), "+f"(d[113]), "+f"(d[114]), "+f"(d[115]), "+f"(d[116]), "+f"(d[117]), "+f"(d[118]), "+f"(d[119])
        : "l"(da), "l"(db), "r"(sd));
}
__device__ __forceinline__ void wgmma_ss80(float (&d)[40], uint64_t da, uint64_t db, int sd) {
    asm volatile("{\n.reg .pred p;\nsetp.ne.b32 p, %42, 0;\n"
        "wgmma.mma_async.sync.aligned.m64n80k16.f32.bf16.bf16 "
        "{%0,%1,%2,%3,%4,%5,%6,%7,%8,%9,%10,%11,%12,%13,%14,%15,%16,%17,%18,%19,"
        "%20,%21,%22,%23,%24,%25,%26,%27,%28,%29,%30,%31,%32,%33,%34,%35,%36,%37,%38,%39}, "
        "%40, %41, p, 1, 1, 0, 1;\n}\n"
        : "+f"(d[0]), "+f"(d[1]), "+f"(d[2]), "+f"(d[3]), "+f"(d[4]), "+f"(d[5]), "+f"(d[6]), "+f"(d[7]), "+f"(d[8]), "+f"(d[9]),
          "+f"(d[10]), "+f"(d[11]), "+f"(d[12]), "+f"(d[13]), "+f"(d[14]), "+f"(d[15]), "+f"(d[16]), "+f"(d[17]), "+f"(d[18]), "+f"(d[19]),
          "+f"(d[20]), "+f"(d[21]), "+f"(d[22]), "+f"(d[23]), "+f"(d[24]), "+f"(d[25]), "+f"(d[26]), "+f"(d[27]), "+f"(d[28]), "+f"(d[29]),
          "+f"(d[30]), "+f"(d[31]), "+f"(d[32]), "+f"(d[33]), "+f"(d[34]), "+f"(d[35]), "+f"(d[36]), "+f"(d[37]), "+f"(d[38]), "+f"(d[39])
        : "l"(da), "l"(db), "r"(sd));
}
__device__ __forceinline__ void wgmma_qk0(float (&d)[32], uint32_t a0, uint32_t a1, uint32_t a2, uint32_t a3, uint64_t db) {
    asm volatile("{\n.reg .pred p;\nsetp.ne.b32 p, 0, 0;\n"
        "wgmma.mma_async.sync.aligned.m64n64k16.f32.bf16.bf16 "
        "{%0,%1,%2,%3,%4,%5,%6,%7,%8,%9,%10,%11,%12,%13,%14,%15,%16,%17,%18,%19,"
        "%20,%21,%22,%23,%24,%25,%26,%27,%28,%29,%30,%31}, "
        "{%32,%33,%34,%35}, %36, p, 1, 1, 0;\n}\n"
        : "=f"(d[0]), "=f"(d[1]), "=f"(d[2]), "=f"(d[3]), "=f"(d[4]), "=f"(d[5]), "=f"(d[6]), "=f"(d[7]), "=f"(d[8]), "=f"(d[9]),
          "=f"(d[10]), "=f"(d[11]), "=f"(d[12]), "=f"(d[13]), "=f"(d[14]), "=f"(d[15]), "=f"(d[16]), "=f"(d[17]), "=f"(d[18]), "=f"(d[19]),
          "=f"(d[20]), "=f"(d[21]), "=f"(d[22]), "=f"(d[23]), "=f"(d[24]), "=f"(d[25]), "=f"(d[26]), "=f"(d[27]), "=f"(d[28]), "=f"(d[29]),
          "=f"(d[30]), "=f"(d[31])
        : "r"(a0), "r"(a1), "r"(a2), "r"(a3), "l"(db));
}
__device__ __forceinline__ void wgmma_qk1(float (&d)[32], uint32_t a0, uint32_t a1, uint32_t a2, uint32_t a3, uint64_t db) {
    asm volatile("{\n.reg .pred p;\nsetp.eq.b32 p, 0, 0;\n"
        "wgmma.mma_async.sync.aligned.m64n64k16.f32.bf16.bf16 "
        "{%0,%1,%2,%3,%4,%5,%6,%7,%8,%9,%10,%11,%12,%13,%14,%15,%16,%17,%18,%19,"
        "%20,%21,%22,%23,%24,%25,%26,%27,%28,%29,%30,%31}, "
        "{%32,%33,%34,%35}, %36, p, 1, 1, 0;\n}\n"
        : "+f"(d[0]), "+f"(d[1]), "+f"(d[2]), "+f"(d[3]), "+f"(d[4]), "+f"(d[5]), "+f"(d[6]), "+f"(d[7]), "+f"(d[8]), "+f"(d[9]),
          "+f"(d[10]), "+f"(d[11]), "+f"(d[12]), "+f"(d[13]), "+f"(d[14]), "+f"(d[15]), "+f"(d[16]), "+f"(d[17]), "+f"(d[18]), "+f"(d[19]),
          "+f"(d[20]), "+f"(d[21]), "+f"(d[22]), "+f"(d[23]), "+f"(d[24]), "+f"(d[25]), "+f"(d[26]), "+f"(d[27]), "+f"(d[28]), "+f"(d[29]),
          "+f"(d[30]), "+f"(d[31])
        : "r"(a0), "r"(a1), "r"(a2), "r"(a3), "l"(db));
}
__device__ __forceinline__ void wgmma_pv(float (&d)[12], uint32_t a0, uint32_t a1, uint32_t a2, uint32_t a3, uint64_t db) {
    asm volatile("{\n.reg .pred p;\nsetp.eq.b32 p, 0, 0;\n"
        "wgmma.mma_async.sync.aligned.m64n24k16.f32.bf16.bf16 "
        "{%0,%1,%2,%3,%4,%5,%6,%7,%8,%9,%10,%11}, "
        "{%12,%13,%14,%15}, %16, p, 1, 1, 1;\n}\n"
        : "+f"(d[0]), "+f"(d[1]), "+f"(d[2]), "+f"(d[3]), "+f"(d[4]), "+f"(d[5]), "+f"(d[6]), "+f"(d[7]), "+f"(d[8]), "+f"(d[9]),
          "+f"(d[10]), "+f"(d[11])
        : "r"(a0), "r"(a1), "r"(a2), "r"(a3), "l"(db));
}

constexpr int K1_STAGES = 4, K1_STAGE_BYTES = 16384 + 32768;
constexpr int K1_SMEM = K1_STAGES * K1_STAGE_BYTES + 1024 + 256;

__global__ void __launch_bounds__(384, 1)
k_qkv(const __grid_constant__ CUtensorMap tmX, const __grid_constant__ CUtensorMap tmWb, const __grid_constant__ CUtensorMap tmWa,
      const __nv_bfloat16* __restrict__ x, const __nv_bfloat16* __restrict__ gate_w) {
    extern __shared__ uint8_t smem_raw[];
    const uint32_t sb = (smem_u32(smem_raw) + 1023) & ~1023u;
    const uint32_t bars = sb + K1_STAGES * K1_STAGE_BYTES;
    const int warp = __shfl_sync(0xffffffffu, threadIdx.x >> 5, 0), lane = threadIdx.x & 31;
    const int bid = blockIdx.x;
    const int mt = (bid >> 4) * 2 + (bid & 1), nt = (bid >> 1) & 7;

    if (threadIdx.x == 0) {
        for (int s = 0; s < K1_STAGES; s++) { mbar_init(bars + 8 * s, 1); mbar_init(bars + 32 + 8 * s, 8); }
        fence_mbar_init();
    }
    __syncthreads();
    pdl_launch();

    if (warp == 8) {
        if (lane == 0) {
            prefetch_tmap(&tmX); prefetch_tmap(&tmWb); prefetch_tmap(&tmWa);
            int s = 0; uint32_t ph = 1;
#pragma unroll 1
            for (int it = 0; it < 20; it++) {
                const int kb = it >= 10 ? it - 10 : it;
                const CUtensorMap* tw = it >= 10 ? &tmWa : &tmWb;
                const uint32_t st = sb + s * K1_STAGE_BYTES, fb = bars + 8 * s;
                mbar_wait(bars + 32 + 8 * s, ph);
                mbar_expect_tx(fb, K1_STAGE_BYTES);
                tma_2d(st, &tmX, kb * 64, mt * 128, fb);
#pragma unroll
                for (int j = 0; j < 4; j++) tma_2d(st + 16384 + j * 8192, tw, nt * 240 + j * 64, kb * 64, fb);
                if (++s == K1_STAGES) { s = 0; ph ^= 1; }
            }
        }
    } else if (warp > 8) {
        const uint32_t* gw = reinterpret_cast<const uint32_t*>(gate_w);
        uint32_t gv[10];
#pragma unroll
        for (int i = 0; i < 10; i++) gv[i] = __ldg(gw + lane + 32 * i);
        for (int r = warp - 9; r < 16; r += 3) {
            const int row = bid * 16 + r;
            const uint32_t* xr = reinterpret_cast<const uint32_t*>(x + (size_t)row * DM);
            float a = 0.f;
#pragma unroll
            for (int i = 0; i < 10; i++) {
                const uint32_t xv = __ldg(xr + lane + 32 * i);
                a = fmaf(bf_lo(xv), bf_lo(gv[i]), a);
                a = fmaf(bf_hi(xv), bf_hi(gv[i]), a);
            }
#pragma unroll
            for (int o = 16; o; o >>= 1) a += __shfl_xor_sync(0xffffffffu, a, o);
            if (lane == 0) g_gate[row] = 1.f / (1.f + __expf(-a));
        }
    } else {
        const int wg = warp >> 2;
        const int t = lane & 3;
        float acc[120];
        int s = 0; uint32_t ph = 0;
#pragma unroll 1
        for (int br = 0; br < 2; br++) {
#pragma unroll
            for (int i = 0; i < 120; i++) acc[i] = 0.f;
            pin(acc);
            int prev = -1;
#pragma unroll 1
            for (int kb = 0; kb < 10; kb++) {
                const uint32_t st = sb + s * K1_STAGE_BYTES;
                const uint64_t da = mkdesc(st + wg * 8192, 16, 1024, 1);
                const uint64_t db = mkdesc(st + 16384, 8192, 1024, 1);
                mbar_wait(bars + 8 * s, ph);
                wg_fence();
#pragma unroll
                for (int k = 0; k < 4; k++) wgmma_ss240(acc, da + k * 2, db + k * 128, 1);
                wg_commit();
                wg_wait<1>();
                if (prev >= 0 && lane == 0) mbar_arrive(bars + 32 + 8 * prev);
                prev = s;
                if (++s == K1_STAGES) { s = 0; ph ^= 1; }
            }
            wg_wait<0>();
            pin(acc);
            if (lane == 0) mbar_arrive(bars + 32 + 8 * prev);
            const int rg0 = mt * 16 + warp * 2;
            uint8_t* gbase = g_qkv + (size_t)br * 96 * HEAD_BYTES + (size_t)(nt * 12) * HEAD_BYTES + rg0 * 384 + lane * 4;
#pragma unroll
            for (int u = 0; u < 6; u++) {
                const int sec = (nt * 6 + u) >> 4;
#pragma unroll
                for (int r = 0; r < 2; r++) {
                    const bool poly = (br == 0) && ((POLY16 >> ((warp * 2 + r) & 15)) & 1);
                    const float sc = sec == 0 ? QSCALE : (sec == 2 && poly) ? -0.5f : 1.f;
                    uint32_t aug;
                    if (sec == 0) aug = br == 0 ? 0x3D2D43C0u : 0u;
                    else if (sec == 1) aug = br == 0 ? (poly ? 0x00003F80u : 0x3F800000u) : 0u;
                    else aug = poly ? 0x0000BF00u : 0x00003F80u;
                    if (t & 1) aug = 0u;
                    uint32_t v[5];
#pragma unroll
                    for (int j = 0; j < 5; j++) v[j] = pack2(acc[(5 * u + j) * 4 + 2 * r] * sc, acc[(5 * u + j) * 4 + 2 * r + 1] * sc);
                    uint8_t* pe = gbase + (size_t)(2 * u) * HEAD_BYTES + r * 384;
                    uint8_t* po = pe + HEAD_BYTES;
                    *reinterpret_cast<uint32_t*>(pe) = v[0];
                    *reinterpret_cast<uint32_t*>(pe + 128) = v[1];
                    *reinterpret_cast<uint32_t*>(pe + 256) = t < 2 ? v[2] : aug;
                    *reinterpret_cast<uint32_t*>(po) = v[3];
                    *reinterpret_cast<uint32_t*>(po + 128) = v[4];
                    *reinterpret_cast<uint32_t*>(po + 256) = t < 2 ? aug : v[2];
                }
            }
        }
    }
}

__device__ __forceinline__ uint32_t exp2_pair_fma(float a, float b) {
    const uint32_t y = __byte_perm(__float_as_uint(a), __float_as_uint(b), 0x6521);
    const uint32_t z = 0xFE7BFE7Bu - y;
    const uint32_t e = hfma2(y, z, 0x3F053F05u);
    return hfma2(y, e, y);
}
template <int MASK> __device__ __forceinline__ void exp_tile(const float (&s)[32], uint32_t (&p)[16]) {
#pragma unroll
    for (int j = 0; j < 8; j++) {
        if ((MASK >> j) & 1) { p[2 * j] = exp2_pair_fma(s[4 * j], s[4 * j + 1]); p[2 * j + 1] = exp2_pair_fma(s[4 * j + 2], s[4 * j + 3]); }
        else { p[2 * j] = pack2(ex2(s[4 * j]), ex2(s[4 * j + 1])); p[2 * j + 1] = pack2(ex2(s[4 * j + 2]), ex2(s[4 * j + 3])); }
    }
}
__device__ __forceinline__ void qk_tile(float (&s)[32], const uint32_t (&q)[8], uint64_t dk0, uint64_t dk1) {
    wgmma_qk0(s, q[0], q[1], q[2], q[3], dk0);
    wgmma_qk1(s, q[4], q[5], q[6], q[7], dk1);
}
__device__ __forceinline__ void pv_tile(float (&o)[12], const uint32_t (&p)[16], uint64_t dv) {
#pragma unroll
    for (int k = 0; k < 4; k++) wgmma_pv(o, p[4 * k], p[4 * k + 1], p[4 * k + 2], p[4 * k + 3], dv + k * 48);
}
__device__ __forceinline__ void store_o(const float (&o)[12], int row, int h, int colbase, float g0, float g1, int lane, float& l0, float& l1) {
    const int odd = h & 1, t = lane & 3;
    const int src = (lane & ~3) | (odd ? 0 : 2);
    l0 = __shfl_sync(0xffffffffu, o[8], src);
    l1 = __shfl_sync(0xffffffffu, o[10], src);
    const float f0 = __fdividef(g0, l0), f1 = __fdividef(g1, l1);
    __nv_bfloat16* p0 = g_att + (size_t)row * 1280 + colbase + 40 * (h >> 1) + 2 * t;
    __nv_bfloat16* p1 = p0 + 8 * 1280;
    const int off = odd ? 24 : 0;
    *reinterpret_cast<uint32_t*>(p0 + off) = pack2(o[0] * f0, o[1] * f0);
    *reinterpret_cast<uint32_t*>(p1 + off) = pack2(o[2] * f1, o[3] * f1);
    *reinterpret_cast<uint32_t*>(p0 + off + 8) = pack2(o[4] * f0, o[5] * f0);
    *reinterpret_cast<uint32_t*>(p1 + off + 8) = pack2(o[6] * f1, o[7] * f1);
    if ((t >= 2) == (odd != 0)) {
        *reinterpret_cast<uint32_t*>(p0 + 16) = pack2(o[8] * f0, o[9] * f0);
        *reinterpret_cast<uint32_t*>(p1 + 16) = pack2(o[10] * f1, o[11] * f1);
    }
}

constexpr int K2_SMEM = 2 * HEAD_BYTES + 24576 + 512 + 128;
constexpr float SCORE_LIMIT2 = 100.f * 100.f;

__global__ void __launch_bounds__(512, 1) k_attn() {
    extern __shared__ uint8_t smem_raw[];
    const uint32_t sb = (smem_u32(smem_raw) + 127) & ~127u;
    const uint32_t sK = sb, sV = sb + HEAD_BYTES, sQ = sb + 2 * HEAD_BYTES, bars = sQ + 24576;
    float* s_misc = reinterpret_cast<float*>(smem_raw + (bars + 128 - smem_u32(smem_raw)));
    const int warp = __shfl_sync(0xffffffffu, threadIdx.x >> 5, 0), lane = threadIdx.x & 31;
    const int h = blockIdx.x >> 2, qb = blockIdx.x & 3;
    const int g = lane >> 2, t = lane & 3;

    if (threadIdx.x == 0) {
        for (int i = 0; i < 9; i++) mbar_init(bars + 8 * i, 1);
        fence_mbar_init();
    }
    __syncthreads();
    pdl_launch();
    pdl_wait();
    if (threadIdx.x == 0) {
        const uint8_t* gq = g_qkv + (size_t)h * HEAD_BYTES + qb * 24576;
        const uint8_t* gk = g_qkv + (size_t)(32 + h) * HEAD_BYTES;
        const uint8_t* gv = g_qkv + (size_t)(64 + h) * HEAD_BYTES;
        mbar_expect_tx(bars + 64, 24576);
        bulk_g2s(sQ, gq, 24576, bars + 64);
#pragma unroll
        for (int c = 0; c < 8; c++) {
            mbar_expect_tx(bars + 8 * c, 24576);
            bulk_g2s(sK + c * 12288, gk + c * 12288, 12288, bars + 8 * c);
            bulk_g2s(sV + c * 12288, gv + c * 12288, 12288, bars + 8 * c);
        }
    }

    {
        const int rg0 = qb * 64 + warp * 4;
        const uint8_t* aq = g_qkv + (size_t)(96 + h) * HEAD_BYTES + rg0 * 384 + lane * 4;
        const uint8_t* ak = aq + (size_t)32 * HEAD_BYTES - 2 * 384;
        const uint8_t* av = ak + (size_t)32 * HEAD_BYTES;
        uint32_t q[4][3], k[6][3], v[6][3];
#pragma unroll
        for (int i = 0; i < 4; i++)
#pragma unroll
            for (int d = 0; d < 3; d++) q[i][d] = *reinterpret_cast<const uint32_t*>(aq + i * 384 + d * 128);
#pragma unroll
        for (int i = 0; i < 6; i++)
#pragma unroll
            for (int d = 0; d < 3; d++) {
                const bool ok = i >= 2 || rg0 > 0;
                k[i][d] = ok ? *reinterpret_cast<const uint32_t*>(ak + i * 384 + d * 128) : 0u;
                v[i][d] = ok ? *reinterpret_cast<const uint32_t*>(av + i * 384 + d * 128) : 0u;
            }
        float gt[4];
#pragma unroll
        for (int i = 0; i < 4; i++) gt[i] = g_gate[(rg0 + i) * 8 + g];
#pragma unroll
        for (int i = 0; i < 6; i++)
#pragma unroll
            for (int d = 0; d < 3; d++) v[i][d] = movm_t(v[i][d]);
        const bool godd = g & 1;
        const bool early = 2 * t > (g & 6);
        const int sh = godd ? 16 : 0;
#pragma unroll
        for (int b = 0; b < 2; b++) {
            float s[4][4];
#pragma unroll
            for (int j = 0; j < 4; j++) {
                s[j][0] = s[j][1] = s[j][2] = s[j][3] = 0.f;
                mma16816(s[j], q[2 * b][0], q[2 * b + 1][0], q[2 * b][1], q[2 * b + 1][1], k[2 * b + j][0], k[2 * b + j][1]);
                mma1688(s[j], q[2 * b][2], q[2 * b + 1][2], k[2 * b + j][2]);
            }
            uint32_t pa[2], pb[2];
#pragma unroll
            for (int r = 0; r < 2; r++) {
                float va = godd ? s[1 + r][2 * r + 1] : s[1 + r][2 * r];
                const float ve = godd ? s[r][2 * r + 1] : s[r][2 * r];
                const float vl = godd ? s[2 + r][2 * r + 1] : s[2 + r][2 * r];
                float vb = early ? ve : vl;
                if (b == 0 && rg0 == 0) {
                    if (r == 0) va = -INFINITY;
                    if (early) vb = -INFINITY;
                }
                float m = fmaxf(va, vb);
                m = fmaxf(m, __shfl_xor_sync(0xffffffffu, m, 1));
                m = fmaxf(m, __shfl_xor_sync(0xffffffffu, m, 2));
                const uint32_t pp = pack2(ex2(va - m), ex2(vb - m));
                pa[r] = (pp & 0xffffu) << sh;
                pb[r] = (pp >> 16) << sh;
            }
            const uint32_t a00 = early ? pb[0] : 0u, a01 = pa[0], a02 = early ? 0u : pb[0];
            const uint32_t a11 = early ? pb[1] : 0u, a12 = pa[1], a13 = early ? 0u : pb[1];
            float o[12];
#pragma unroll
            for (int d = 0; d < 3; d++) {
                float c[4] = {0.f, 0.f, 0.f, 0.f};
                mma16816(c, a00, 0u, a01, a11, v[2 * b][d], v[2 * b + 1][d]);
                mma16816(c, a02, a12, 0u, a13, v[2 * b + 2][d], v[2 * b + 3][d]);
                o[4 * d] = c[0]; o[4 * d + 1] = c[1]; o[4 * d + 2] = c[2]; o[4 * d + 3] = c[3];
            }
            float l0, l1;
            store_o(o, (rg0 + 2 * b) * 8 + g, h, 0, gt[2 * b], gt[2 * b + 1], lane, l0, l1);
        }
    }

    const uint64_t dK0 = mkdesc(sK, 128, 384, 0), dK1 = mkdesc(sK + 256, 0, 384, 0), dV = mkdesc(sV, 384, 128, 0);
    constexpr int TS = 8 * 24;
    const bool aug_lane = (t >= 2) != ((h & 1) != 0);
    mbar_wait(bars + 64, 0);
#pragma unroll 1
    for (int u = 0; u < 2; u++) {
        const int lrg = u * 32 + warp * 2;
        uint32_t q[8];
        {
            const uint32_t a = sQ + lrg * 384 + lane * 4;
            q[0] = lds32(a); q[1] = lds32(a + 384); q[2] = lds32(a + 128); q[3] = lds32(a + 512);
            q[4] = lds32(a + 256); q[5] = lds32(a + 640); q[6] = 0u; q[7] = 0u;
            const uint32_t c0 = aug_lane ? 0u : q[4], c1 = aug_lane ? 0u : q[5];
            float n0 = bf_lo(q[0]) * bf_lo(q[0]) + bf_hi(q[0]) * bf_hi(q[0]) + bf_lo(q[2]) * bf_lo(q[2]) + bf_hi(q[2]) * bf_hi(q[2]) + bf_lo(c0) * bf_lo(c0) + bf_hi(c0) * bf_hi(c0);
            float n1 = bf_lo(q[1]) * bf_lo(q[1]) + bf_hi(q[1]) * bf_hi(q[1]) + bf_lo(q[3]) * bf_lo(q[3]) + bf_hi(q[3]) * bf_hi(q[3]) + bf_lo(c1) * bf_lo(c1) + bf_hi(c1) * bf_hi(c1);
            n0 += __shfl_xor_sync(0xffffffffu, n0, 1); n1 += __shfl_xor_sync(0xffffffffu, n1, 1);
            n0 += __shfl_xor_sync(0xffffffffu, n0, 2); n1 += __shfl_xor_sync(0xffffffffu, n1, 2);
            const uint32_t nm = __reduce_max_sync(0xffffffffu, max(__float_as_uint(n0), __float_as_uint(n1)));
            if (lane == 0) s_misc[16 + u * 16 + warp] = __uint_as_float(nm);
        }
        float o[12];
#pragma unroll
        for (int i = 0; i < 12; i++) o[i] = 0.f;
        pin(o); pin(q);
        float s0[32], s1[32];
        uint32_t p[16];
        mbar_wait(bars, 0);
        wg_fence(); qk_tile(s0, q, dK0, dK1); wg_commit();
#pragma unroll
        for (int j = 0; j < 32; j += 2) {
            wg_fence(); qk_tile(s1, q, dK0 + (j + 1) * TS, dK1 + (j + 1) * TS); wg_commit();
            wg_wait<1>(); pin(s0);
            exp_tile<POLY16 & 0xff>(s0, p);
            pin(p);
            wg_fence(); pv_tile(o, p, dV + j * TS); wg_commit();
            if (j + 2 < 32) {
                if (((j + 2) & 3) == 0) mbar_wait(bars + 8 * ((j + 2) >> 2), 0);
                wg_fence(); qk_tile(s0, q, dK0 + (j + 2) * TS, dK1 + (j + 2) * TS); wg_commit();
                wg_wait<1>();
            } else {
                wg_wait<0>();
            }
            pin(s1);
            exp_tile<(POLY16 >> 8)>(s1, p);
            pin(p);
            wg_fence(); pv_tile(o, p, dV + (j + 1) * TS); wg_commit();
        }
        const int row = qb * 512 + lrg * 8 + g;
        const float g0 = 1.f - g_gate[row], g1 = 1.f - g_gate[row + 8];
        wg_wait<0>(); pin(o);
        float l0, l1;
        store_o(o, row, h, 640, g0, g1, lane, l0, l1);
        float mx = 0.f;
#pragma unroll
        for (int i = 0; i < 12; i++) mx = fmaxf(mx, fabsf(o[i])) + (o[i] - o[i]);
        const bool bad = !(l0 >= 9.3132257e-10f && l1 >= 9.3132257e-10f && mx <= 1e37f);
        const uint32_t anybad = __ballot_sync(0xffffffffu, bad);
        if (lane == 0) s_misc[48 + u * 16 + warp] = anybad ? 1.f : 0.f;
        if (u == 0) {
            uint32_t km = 0;
#pragma unroll
            for (int i = 0; i < 4; i++) {
                const int key = i * 512 + threadIdx.x;
                const uint32_t a = sK + (key >> 3) * 384 + (key & 7) * 16;
                const uint4 k0 = lds128(a), k1 = lds128(a + 128), k2 = lds128(a + 256);
                const uint32_t w[10] = {k0.x, k0.y, k0.z, k0.w, k1.x, k1.y, k1.z, k1.w, (h & 1) ? k2.z : k2.x, (h & 1) ? k2.w : k2.y};
                float n = 0.f;
#pragma unroll
                for (int e = 0; e < 10; e++) n += bf_lo(w[e]) * bf_lo(w[e]) + bf_hi(w[e]) * bf_hi(w[e]);
                km = max(km, __float_as_uint(n));
            }
            km = __reduce_max_sync(0xffffffffu, km);
            if (lane == 0) s_misc[warp] = __uint_as_float(km);
        }
    }

    __syncthreads();
    const float kn = __uint_as_float(__reduce_max_sync(0xffffffffu, __float_as_uint(s_misc[lane & 15])));
#pragma unroll 1
    for (int u = 0; u < 2; u++) {
        if (s_misc[16 + u * 16 + warp] * kn <= SCORE_LIMIT2 && s_misc[48 + u * 16 + warp] == 0.f) continue;
        const int lrg = u * 32 + warp * 2;
        const uint32_t a = sQ + lrg * 384 + lane * 4;
        const uint32_t q0 = lds32(a), q1 = lds32(a + 384), q2 = lds32(a + 128), q3 = lds32(a + 512);
        const uint32_t q4 = aug_lane ? 0u : lds32(a + 256), q5 = aug_lane ? 0u : lds32(a + 640);
        float m0 = -INFINITY, m1 = -INFINITY;
#pragma unroll 2
        for (int kg = 0; kg < 256; kg++) {
            const uint32_t ka = sK + kg * 384 + lane * 4;
            float c[4] = {0.f, 0.f, 0.f, 0.f};
            mma16816(c, q0, q1, q2, q3, lds32(ka), lds32(ka + 128));
            mma1688(c, q4, q5, lds32(ka + 256));
            m0 = fmaxf(m0, fmaxf(c[0], c[1])); m1 = fmaxf(m1, fmaxf(c[2], c[3]));
        }
        m0 = fmaxf(m0, __shfl_xor_sync(0xffffffffu, m0, 1)); m1 = fmaxf(m1, __shfl_xor_sync(0xffffffffu, m1, 1));
        m0 = fmaxf(m0, __shfl_xor_sync(0xffffffffu, m0, 2)); m1 = fmaxf(m1, __shfl_xor_sync(0xffffffffu, m1, 2));
        float oc[3][4];
#pragma unroll
        for (int d = 0; d < 3; d++) oc[d][0] = oc[d][1] = oc[d][2] = oc[d][3] = 0.f;
#pragma unroll 1
        for (int kg = 0; kg < 256; kg += 2) {
            uint32_t pp[2][2];
#pragma unroll
            for (int e = 0; e < 2; e++) {
                const uint32_t ka = sK + (kg + e) * 384 + lane * 4;
                float c[4] = {0.f, 0.f, 0.f, 0.f};
                mma16816(c, q0, q1, q2, q3, lds32(ka), lds32(ka + 128));
                mma1688(c, q4, q5, lds32(ka + 256));
                const float f = ((POLY16 >> ((kg + e) & 15)) & 1) ? -2.f : 1.f;
                pp[e][0] = pack2(f * ex2(c[0] - m0), f * ex2(c[1] - m0));
                pp[e][1] = pack2(f * ex2(c[2] - m1), f * ex2(c[3] - m1));
            }
            const uint32_t va = sV + kg * 384 + lane * 4;
#pragma unroll
            for (int d = 0; d < 3; d++)
                mma16816(oc[d], pp[0][0], pp[0][1], pp[1][0], pp[1][1], movm_t(lds32(va + d * 128)), movm_t(lds32(va + 384 + d * 128)));
        }
        float o[12];
#pragma unroll
        for (int i = 0; i < 12; i++) o[i] = oc[i >> 2][i & 3];
        const int row = qb * 512 + lrg * 8 + g;
        float l0, l1;
        store_o(o, row, h, 640, 1.f - g_gate[row], 1.f - g_gate[row + 8], lane, l0, l1);
    }
}

constexpr int K3_STAGES = 8, K3_STAGE_BYTES = 16384 + 10240;
constexpr int K3_SMEM = K3_STAGES * K3_STAGE_BYTES + 1024 + 256;

__global__ void __launch_bounds__(288, 1)
k_out(const __grid_constant__ CUtensorMap tmA, const __grid_constant__ CUtensorMap tmWa, const __grid_constant__ CUtensorMap tmWb,
      __nv_bfloat16* __restrict__ out) {
    extern __shared__ uint8_t smem_raw[];
    const uint32_t sb = (smem_u32(smem_raw) + 1023) & ~1023u;
    const uint32_t bars = sb + K3_STAGES * K3_STAGE_BYTES;
    const int warp = __shfl_sync(0xffffffffu, threadIdx.x >> 5, 0), lane = threadIdx.x & 31;
    const int mt = blockIdx.x >> 3, nt = blockIdx.x & 7;
    if (threadIdx.x == 0) {
        for (int s = 0; s < K3_STAGES; s++) { mbar_init(bars + 8 * s, 1); mbar_init(bars + 64 + 8 * s, 8); }
        fence_mbar_init();
    }
    __syncthreads();
    if (warp == 8) {
        if (lane == 0) {
            prefetch_tmap(&tmA); prefetch_tmap(&tmWa); prefetch_tmap(&tmWb);
#pragma unroll 1
            for (int it = 0; it < K3_STAGES; it++) {
                mbar_expect_tx(bars + 8 * it, K3_STAGE_BYTES);
                tma_3d(sb + it * K3_STAGE_BYTES + 16384, &tmWa, 0, it * 64, nt * 5, bars + 8 * it);
            }
            pdl_wait();
#pragma unroll 1
            for (int it = 0; it < K3_STAGES; it++) tma_2d(sb + it * K3_STAGE_BYTES, &tmA, it * 64, mt * 128, bars + 8 * it);
            int s = 0; uint32_t ph = 0;
#pragma unroll 1
            for (int it = K3_STAGES; it < 20; it++) {
                const uint32_t st = sb + s * K3_STAGE_BYTES, fb = bars + 8 * s;
                mbar_wait(bars + 64 + 8 * s, ph);
                mbar_expect_tx(fb, K3_STAGE_BYTES);
                tma_2d(st, &tmA, it * 64, mt * 128, fb);
                tma_3d(st + 16384, it >= 10 ? &tmWb : &tmWa, 0, (it >= 10 ? it - 10 : it) * 64, nt * 5, fb);
                if (++s == K3_STAGES) { s = 0; ph ^= 1; }
            }
        }
    } else {
        const int wg = warp >> 2;
        float acc[40];
#pragma unroll
        for (int i = 0; i < 40; i++) acc[i] = 0.f;
        pin(acc);
        int s = 0, prev = -1; uint32_t ph = 0;
#pragma unroll 1
        for (int kb = 0; kb < 20; kb++) {
            const uint32_t st = sb + s * K3_STAGE_BYTES;
            const uint64_t da = mkdesc(st + wg * 8192, 16, 1024, 1);
            const uint64_t db = mkdesc(st + 16384, 2048, 256, 3);
            mbar_wait(bars + 8 * s, ph);
            wg_fence();
#pragma unroll
            for (int k = 0; k < 4; k++) wgmma_ss80(acc, da + k * 2, db + k * 32, 1);
            wg_commit();
            wg_wait<1>();
            if (prev >= 0 && lane == 0) mbar_arrive(bars + 64 + 8 * prev);
            prev = s;
            if (++s == K3_STAGES) { s = 0; ph ^= 1; }
        }
        wg_wait<0>();
        pin(acc);
        __nv_bfloat16* p0 = out + (size_t)(mt * 128 + warp * 16 + (lane >> 2)) * DM + nt * 80 + (lane & 3) * 2;
#pragma unroll
        for (int j = 0; j < 10; j++) {
            *reinterpret_cast<uint32_t*>(p0 + j * 8) = pack2(acc[4 * j], acc[4 * j + 1]);
            *reinterpret_cast<uint32_t*>(p0 + 8 * DM + j * 8) = pack2(acc[4 * j + 2], acc[4 * j + 3]);
        }
    }
}

typedef CUresult (*EncodeFn)(CUtensorMap*, CUtensorMapDataType, cuuint32_t, void*, const cuuint64_t*, const cuuint64_t*,
                             const cuuint32_t*, const cuuint32_t*, CUtensorMapInterleave, CUtensorMapSwizzle,
                             CUtensorMapL2promotion, CUtensorMapFloatOOBfill);

void make_map(EncodeFn fn, CUtensorMap* tm, const void* ptr, int rank, const cuuint64_t* dims, const cuuint64_t* strides,
              const cuuint32_t* box, CUtensorMapSwizzle swz) {
    const cuuint32_t es[3] = {1, 1, 1};
    fn(tm, CU_TENSOR_MAP_DATA_TYPE_BFLOAT16, rank, const_cast<void*>(ptr), dims, strides, box, es, CU_TENSOR_MAP_INTERLEAVE_NONE,
       swz, CU_TENSOR_MAP_L2_PROMOTION_L2_256B, CU_TENSOR_MAP_FLOAT_OOB_FILL_NONE);
}

}

extern "C" void kernel_launch(void* const* d_in, const int* in_sizes, int n_in, void* d_out, int out_size) {
    (void)in_sizes; (void)n_in; (void)out_size;
    const __nv_bfloat16* x = (const __nv_bfloat16*)d_in[0];
    const __nv_bfloat16* wqkv_a = (const __nv_bfloat16*)d_in[1];
    const __nv_bfloat16* wo_a = (const __nv_bfloat16*)d_in[2];
    const __nv_bfloat16* wqkv_b = (const __nv_bfloat16*)d_in[4];
    const __nv_bfloat16* wo_b = (const __nv_bfloat16*)d_in[5];
    const __nv_bfloat16* gate_w = (const __nv_bfloat16*)d_in[6];

    void* fnp = nullptr;
    cudaDriverEntryPointQueryResult qr;
    cudaGetDriverEntryPoint("cuTensorMapEncodeTiled", &fnp, cudaEnableDefault, &qr);
    EncodeFn enc = (EncodeFn)fnp;
    void* att = nullptr;
    cudaGetSymbolAddress(&att, g_att);

    CUtensorMap tmX, tmWb, tmWa, tmAtt, tmOa, tmOb;
    {
        const cuuint64_t d[2] = {640, 2048}, s[1] = {1280};
        const cuuint32_t b[2] = {64, 128};
        make_map(enc, &tmX, x, 2, d, s, b, CU_TENSOR_MAP_SWIZZLE_128B);
    }
    {
        const cuuint64_t d[2] = {1920, 640}, s[1] = {3840};
        const cuuint32_t b[2] = {64, 64};
        make_map(enc, &tmWb, wqkv_b, 2, d, s, b, CU_TENSOR_MAP_SWIZZLE_128B);
        make_map(enc, &tmWa, wqkv_a, 2, d, s, b, CU_TENSOR_MAP_SWIZZLE_128B);
    }
    {
        const cuuint64_t d[2] = {1280, 2048}, s[1] = {2560};
        const cuuint32_t b[2] = {64, 128};
        make_map(enc, &tmAtt, att, 2, d, s, b, CU_TENSOR_MAP_SWIZZLE_128B);
    }
    {
        const cuuint64_t d[3] = {16, 640, 40}, s[2] = {1280, 32};
        const cuuint32_t b[3] = {16, 64, 5};
        make_map(enc, &tmOa, wo_a, 3, d, s, b, CU_TENSOR_MAP_SWIZZLE_32B);
        make_map(enc, &tmOb, wo_b, 3, d, s, b, CU_TENSOR_MAP_SWIZZLE_32B);
    }
    cudaFuncSetAttribute(k_qkv, cudaFuncAttributeMaxDynamicSharedMemorySize, K1_SMEM);
    cudaFuncSetAttribute(k_attn, cudaFuncAttributeMaxDynamicSharedMemorySize, K2_SMEM);
    cudaFuncSetAttribute(k_out, cudaFuncAttributeMaxDynamicSharedMemorySize, K3_SMEM);

    cudaStream_t st = cudaStreamPerThread;
    cudaLaunchAttribute pdl[1];
    pdl[0].id = cudaLaunchAttributeProgrammaticStreamSerialization;
    pdl[0].val.programmaticStreamSerializationAllowed = 1;

    cudaLaunchConfig_t c1 = {};
    c1.gridDim = dim3(128); c1.blockDim = dim3(384); c1.dynamicSmemBytes = K1_SMEM; c1.stream = st;
    cudaLaunchKernelEx(&c1, k_qkv, tmX, tmWb, tmWa, x, gate_w);

    cudaLaunchConfig_t c2 = {};
    c2.gridDim = dim3(128); c2.blockDim = dim3(512); c2.dynamicSmemBytes = K2_SMEM; c2.stream = st; c2.attrs = pdl; c2.numAttrs = 1;
    cudaLaunchKernelEx(&c2, k_attn);

    cudaLaunchConfig_t c3 = {};
    c3.gridDim = dim3(128); c3.blockDim = dim3(288); c3.dynamicSmemBytes = K3_SMEM; c3.stream = st; c3.attrs = pdl; c3.numAttrs = 1;
    cudaLaunchKernelEx(&c3, k_out, tmAtt, tmOa, tmOb, (__nv_bfloat16*)d_out);
}
```

```cpp
#include <cuda_runtime.h>
#include <cuda_bf16.h>
#include <cuda.h>
#include <stdint.h>

namespace {

constexpr int SEQ = 2048, DM = 640;
constexpr int HEAD_BYTES = 256 * 384;
constexpr uint32_t POLY16 = 0xb5bbu;
constexpr float QSCALE = 0.22360679774997896f * 1.4426950408889634f;

__device__ __align__(1024) uint8_t g_qkv[2 * 96 * HEAD_BYTES];
__device__ __align__(128) float g_gate[SEQ];
__device__ __align__(128) float g_nrm[16 * 96];
enum { F_QKVB = 0, F_QKVA = 8, F_HELP = 16, F_ATTA = 17, F_ATTB = 21, F_EXIT = 25, F_COUNT = 26 };
__device__ uint32_t g_flag[F_COUNT * 32];
__device__ __align__(1024) uint4 g_wo[8 * 160 * 10 * 8];
__device__ __align__(1024) uint2 g_att[32 * 160 * 128];

#define TR(i, cond)
#define TRINIT()
#define TRFLUSH()
#define TR2(i, c) TR(i, c)
__device__ __forceinline__ uint32_t smem_u32(const void* p) { return (uint32_t)__cvta_generic_to_shared(p); }
__device__ __forceinline__ void mbar_init(uint32_t bar, int cnt) { asm volatile("mbarrier.init.shared::cta.b64 [%0], %1;" ::"r"(bar), "r"(cnt) : "memory"); }
__device__ __forceinline__ void mbar_expect_tx(uint32_t bar, int bytes) { asm volatile("mbarrier.arrive.expect_tx.shared::cta.b64 _, [%0], %1;" ::"r"(bar), "r"(bytes) : "memory"); }
__device__ __forceinline__ void mbar_arrive(uint32_t bar) { asm volatile("mbarrier.arrive.shared::cta.b64 _, [%0];" ::"r"(bar) : "memory"); }
__device__ __forceinline__ bool mbar_try(uint32_t bar, uint32_t parity) {
    uint32_t ok;
    asm volatile("{\n.reg .pred p;\nmbarrier.try_wait.parity.shared::cta.b64 p, [%1], %2;\nselp.u32 %0, 1, 0, p;\n}\n" : "=r"(ok) : "r"(bar), "r"(parity) : "memory");
    return ok;
}
__device__ __forceinline__ void mbar_wait(uint32_t bar, uint32_t parity) {
    if (mbar_try(bar, parity)) return;
#pragma unroll 1
    for (int i = 0; i < (1 << 21); i++)
        if (mbar_try(bar, parity)) return;
    __trap();
}
__device__ __forceinline__ void fence_mbar_init() { asm volatile("fence.mbarrier_init.release.cluster;" ::: "memory"); }
__device__ __forceinline__ void tma_2d(uint32_t dst, const CUtensorMap* tm, int c0, int c1, uint32_t bar) {
    asm volatile("cp.async.bulk.tensor.2d.shared::cluster.global.mbarrier::complete_tx::bytes [%0], [%1, {%2, %3}], [%4];"
                 ::"r"(dst), "l"(tm), "r"(c0), "r"(c1), "r"(bar) : "memory");
}
__device__ __forceinline__ void tma_3d_mc(uint32_t dst, const CUtensorMap* tm, int c0, int c1, int c2, uint32_t bar, uint16_t mask) {
    asm volatile("cp.async.bulk.tensor.3d.shared::cluster.global.mbarrier::complete_tx::bytes.multicast::cluster [%0], [%1, {%2, %3, %4}], [%5], %6;"
                 ::"r"(dst), "l"(tm), "r"(c0), "r"(c1), "r"(c2), "r"(bar), "h"(mask) : "memory");
}
__device__ __forceinline__ void mbar_arrive_cluster(uint32_t bar, uint32_t cta) {
    asm volatile("{\n.reg .b32 ra;\nmapa.shared::cluster.u32 ra, %0, %1;\nmbarrier.arrive.shared::cluster.b64 _, [ra];\n}\n" ::"r"(bar), "r"(cta) : "memory");
}
__device__ __forceinline__ void tma_store_3d(const CUtensorMap* tm, uint32_t src, int c0, int c1, int c2) {
    asm volatile("cp.async.bulk.tensor.3d.global.shared::cta.bulk_group [%0, {%2, %3, %4}], [%1];" ::"l"(tm), "r"(src), "r"(c0), "r"(c1), "r"(c2) : "memory");
}
__device__ __forceinline__ void cluster_arrive() { asm volatile("barrier.cluster.arrive.relaxed.aligned;" ::: "memory"); }
__device__ __forceinline__ void cluster_wait() { asm volatile("barrier.cluster.wait.aligned;" ::: "memory"); }
__device__ __forceinline__ void named_sync(int id, int n) { asm volatile("bar.sync %0, %1;" ::"r"(id), "r"(n) : "memory"); }
__device__ __forceinline__ void flag_add(uint32_t* p) { asm volatile("red.release.gpu.global.add.u32 [%0], 1;" ::"l"(p) : "memory"); }
__device__ __forceinline__ void flag_add_done(uint32_t* p) { asm volatile("red.relaxed.gpu.global.add.u32 [%0], 1;" ::"l"(p) : "memory"); }
__device__ __forceinline__ void flag_wait(const uint32_t* p, uint32_t target) {
#pragma unroll 1
    for (int i = 0; i < (1 << 22); i++) {
        uint32_t v;
        asm volatile("ld.acquire.gpu.global.u32 %0, [%1];" : "=r"(v) : "l"(p) : "memory");
        if (v >= target) return;
        __nanosleep(40);
    }
    __trap();
}
__device__ __forceinline__ void flag_wait_head(const uint32_t* base, int h, uint32_t help_target) {
    const uint32_t *p0 = base + (h / 12) * 32, *p1 = base + ((32 + h) / 12) * 32, *p2 = base + ((64 + h) / 12) * 32;
    const uint32_t target = 16;
#pragma unroll 1
    for (int i = 0; i < (1 << 22); i++) {
        uint32_t v0, v1, v2, v3;
        asm volatile("ld.relaxed.gpu.global.u32 %0, [%1];" : "=r"(v3) : "l"(g_flag + F_HELP * 32) : "memory");
        asm volatile("ld.relaxed.gpu.global.u32 %0, [%1];" : "=r"(v0) : "l"(p0) : "memory");
        asm volatile("ld.relaxed.gpu.global.u32 %0, [%1];" : "=r"(v1) : "l"(p1) : "memory");
        asm volatile("ld.relaxed.gpu.global.u32 %0, [%1];" : "=r"(v2) : "l"(p2) : "memory");
        if (v0 >= target && v1 >= target && v2 >= target && v3 >= help_target) { asm volatile("fence.acquire.gpu;" ::: "memory"); return; }
        __nanosleep(40);
    }
    __trap();
}
__device__ __forceinline__ uint32_t ld_relaxed(const uint32_t* p) { uint32_t v; asm volatile("ld.relaxed.gpu.global.u32 %0, [%1];" : "=r"(v) : "l"(p) : "memory"); return v; }
__device__ __forceinline__ float ldcg_f32(const float* p) { float v; asm volatile("ld.global.cg.f32 %0, [%1];" : "=f"(v) : "l"(p) : "memory"); return v; }
__device__ __forceinline__ uint32_t ldcg_u32(const void* p) { uint32_t v; asm volatile("ld.global.cg.b32 %0, [%1];" : "=r"(v) : "l"(p) : "memory"); return v; }
__device__ __forceinline__ void bulk_g2s(uint32_t dst, const void* src, int bytes, uint32_t bar) {
    asm volatile("cp.async.bulk.shared::cluster.global.mbarrier::complete_tx::bytes [%0], [%1], %2, [%3];"
                 ::"r"(dst), "l"(src), "r"(bytes), "r"(bar) : "memory");
}
__device__ __forceinline__ void bulk_s2g(void* dst, uint32_t src, int bytes) {
    asm volatile("cp.async.bulk.global.shared::cta.bulk_group [%0], [%1], %2;" ::"l"(dst), "r"(src), "r"(bytes) : "memory");
}
__device__ __forceinline__ void bulk_commit() { asm volatile("cp.async.bulk.commit_group;" ::: "memory"); }
__device__ __forceinline__ void bulk_wait_read() { asm volatile("cp.async.bulk.wait_group.read 0;" ::: "memory"); }
__device__ __forceinline__ void bulk_wait_all() { asm volatile("cp.async.bulk.wait_group 0;" ::: "memory"); }
__device__ __forceinline__ void l2_prefetch(const void* p, int bytes) { asm volatile("cp.async.bulk.prefetch.L2.global [%0], %1;" ::"l"(p), "r"(bytes) : "memory"); }
__device__ __forceinline__ void fence_async_smem() { asm volatile("fence.proxy.async.shared::cta;" ::: "memory"); }
__device__ __forceinline__ void stsm4(uint32_t a, uint32_t r0, uint32_t r1, uint32_t r2, uint32_t r3) {
    asm volatile("stmatrix.sync.aligned.m8n8.x4.shared.b16 [%0], {%1,%2,%3,%4};" ::"r"(a), "r"(r0), "r"(r1), "r"(r2), "r"(r3) : "memory");
}
__device__ __forceinline__ void prefetch_tmap(const CUtensorMap* tm) { asm volatile("prefetch.tensormap [%0];" ::"l"(tm) : "memory"); }
__device__ __forceinline__ void wg_fence() { asm volatile("wgmma.fence.sync.aligned;" ::: "memory"); }
__device__ __forceinline__ void wg_commit() { asm volatile("wgmma.commit_group.sync.aligned;" ::: "memory"); }
template <int N> __device__ __forceinline__ void wg_wait() { asm volatile("wgmma.wait_group.sync.aligned %0;" ::"n"(N) : "memory"); }
__device__ __forceinline__ uint64_t mkdesc(uint32_t addr, uint32_t lbo, uint32_t sbo, uint32_t swz) {
    return (uint64_t)((addr & 0x3FFFF) >> 4) | ((uint64_t)(lbo >> 4) << 16) | ((uint64_t)(sbo >> 4) << 32) | ((uint64_t)swz << 62);
}
template <int N> __device__ __forceinline__ void pin(float (&r)[N]) {
#pragma unroll
    for (int i = 0; i < N; i++) asm volatile("" : "+f"(r[i])::"memory");
}
template <int N> __device__ __forceinline__ void pin(uint32_t (&r)[N]) {
#pragma unroll
    for (int i = 0; i < N; i++) asm volatile("" : "+r"(r[i])::"memory");
}
__device__ __forceinline__ float ex2(float x) { float y; asm("ex2.approx.ftz.f32 %0, %1;" : "=f"(y) : "f"(x)); return y; }
__device__ __forceinline__ uint32_t pack2(float lo, float hi) { uint32_t r; asm("cvt.rn.bf16x2.f32 %0, %1, %2;" : "=r"(r) : "f"(hi), "f"(lo)); return r; }
__device__ __forceinline__ uint32_t hfma2(uint32_t a, uint32_t b, uint32_t c) { uint32_t d; asm("fma.rn.bf16x2 %0, %1, %2, %3;" : "=r"(d) : "r"(a), "r"(b), "r"(c)); return d; }
__device__ __forceinline__ float bf_lo(uint32_t v) { return __uint_as_float(v << 16); }
__device__ __forceinline__ float bf_hi(uint32_t v) { return __uint_as_float(v & 0xffff0000u); }
__device__ __forceinline__ void mma16816(float (&c)[4], uint32_t a0, uint32_t a1, uint32_t a2, uint32_t a3, uint32_t b0, uint32_t b1) {
    asm volatile("mma.sync.aligned.m16n8k16.row.col.f32.bf16.bf16.f32 {%0,%1,%2,%3}, {%4,%5,%6,%7}, {%8,%9}, {%0,%1,%2,%3};"
                 : "+f"(c[0]), "+f"(c[1]), "+f"(c[2]), "+f"(c[3]) : "r"(a0), "r"(a1), "r"(a2), "r"(a3), "r"(b0), "r"(b1));
}
__device__ __forceinline__ void mma1688(float (&c)[4], uint32_t a0, uint32_t a1, uint32_t b0) {
    asm volatile("mma.sync.aligned.m16n8k8.row.col.f32.bf16.bf16.f32 {%0,%1,%2,%3}, {%4,%5}, {%6}, {%0,%1,%2,%3};"
                 : "+f"(c[0]), "+f"(c[1]), "+f"(c[2]), "+f"(c[3]) : "r"(a0), "r"(a1), "r"(b0));
}
__device__ __forceinline__ uint32_t movm_t(uint32_t a) { uint32_t d; asm volatile("movmatrix.sync.aligned.m8n8.trans.b16 %0, %1;" : "=r"(d) : "r"(a)); return d; }
__device__ __forceinline__ void stg128(void* p, uint4 v) { asm volatile("st.global.v4.b32 [%0], {%1,%2,%3,%4};" ::"l"(p), "r"(v.x), "r"(v.y), "r"(v.z), "r"(v.w) : "memory"); }
__device__ __forceinline__ void stg64(void* p, uint32_t a, uint32_t b) { asm volatile("st.global.v2.b32 [%0], {%1,%2};" ::"l"(p), "r"(a), "r"(b) : "memory"); }
__device__ __forceinline__ int frag_pos(int warp4, int lane) { return ((lane & 2) << 5) | (warp4 << 4) | ((lane >> 2) << 1) | (lane & 1); }
__device__ __forceinline__ void sts64(uint32_t a, uint32_t x, uint32_t y) { asm volatile("st.shared.v2.b32 [%0], {%1,%2};" ::"r"(a), "r"(x), "r"(y) : "memory"); }
__device__ __forceinline__ bool named_sync_or(int id, int n, bool p) {
    uint32_t r;
    asm volatile("{\n.reg .pred a, b;\nsetp.ne.u32 a, %3, 0;\nbar.red.or.pred b, %1, %2, a;\nselp.u32 %0, 1, 0, b;\n}\n" : "=r"(r) : "r"(id), "r"(n), "r"((uint32_t)p) : "memory");
    return r;
}
__device__ __forceinline__ uint32_t clock_lo() { uint32_t v; asm volatile("mov.u32 %0, %%clock;" : "=r"(v)); return v; }
__device__ __forceinline__ int fresh_bid() { int v; asm volatile("mov.u32 %0, %%ctaid.x;" : "=r"(v)); return v; }
__device__ __forceinline__ int fresh_tid() { int v; asm volatile("mov.u32 %0, %%tid.x;" : "=r"(v)); return v; }
__device__ __forceinline__ uint32_t lds32(uint32_t a) { uint32_t v; asm volatile("ld.shared.b32 %0, [%1];" : "=r"(v) : "r"(a)); return v; }
__device__ __forceinline__ uint4 lds128(uint32_t a) { uint4 v; asm volatile("ld.shared.v4.b32 {%0,%1,%2,%3}, [%4];" : "=r"(v.x), "=r"(v.y), "=r"(v.z), "=r"(v.w) : "r"(a)); return v; }

__device__ __forceinline__ void wgmma_ss128(float (&d)[64], uint64_t da, uint64_t db) {
    asm volatile("{\n.reg .pred p;\nsetp.eq.b32 p, 0, 0;\n"
        "wgmma.mma_async.sync.aligned.m64n128k16.f32.bf16.bf16 "
        "{%0,%1,%2,%3,%4,%5,%6,%7,%8,%9,%10,%11,%12,%13,%14,%15,%16,%17,%18,%19,"
        "%20,%21,%22,%23,%24,%25,%26,%27,%28,%29,%30,%31,%32,%33,%34,%35,%36,%37,%38,%39,"
        "%40,%41,%42,%43,%44,%45,%46,%47,%48,%49,%50,%51,%52,%53,%54,%55,%56,%57,%58,%59,"
        "%60,%61,%62,%63}, "
        "%64, %65, p, 1, 1, 0, 1;\n}\n"
        : "+f"(d[0]), "+f"(d[1]), "+f"(d[2]), "+f"(d[3]), "+f"(d[4]), "+f"(d[5]), "+f"(d[6]), "+f"(d[7]), "+f"(d[8]), "+f"(d[9]),
          "+f"(d[10]), "+f"(d[11]), "+f"(d[12]), "+f"(d[13]), "+f"(d[14]), "+f"(d[15]), "+f"(d[16]), "+f"(d[17]), "+f"(d[18]), "+f"(d[19]),
          "+f"(d[20]), "+f"(d[21]), "+f"(d[22]), "+f"(d[23]), "+f"(d[24]), "+f"(d[25]), "+f"(d[26]), "+f"(d[27]), "+f"(d[28]), "+f"(d[29]),
          "+f"(d[30]), "+f"(d[31]), "+f"(d[32]), "+f"(d[33]), "+f"(d[34]), "+f"(d[35]), "+f"(d[36]), "+f"(d[37]), "+f"(d[38]), "+f"(d[39]),
          "+f"(d[40]), "+f"(d[41]), "+f"(d[42]), "+f"(d[43]), "+f"(d[44]), "+f"(d[45]), "+f"(d[46]), "+f"(d[47]), "+f"(d[48]), "+f"(d[49]),
          "+f"(d[50]), "+f"(d[51]), "+f"(d[52]), "+f"(d[53]), "+f"(d[54]), "+f"(d[55]), "+f"(d[56]), "+f"(d[57]), "+f"(d[58]), "+f"(d[59]),
          "+f"(d[60]), "+f"(d[61]), "+f"(d[62]), "+f"(d[63])
        : "l"(da), "l"(db));
}
__device__ __forceinline__ void wgmma_ss112(float (&d)[56], uint64_t da, uint64_t db) {
    asm volatile("{\n.reg .pred p;\nsetp.eq.b32 p, 0, 0;\n"
        "wgmma.mma_async.sync.aligned.m64n112k16.f32.bf16.bf16 "
        "{%0,%1,%2,%3,%4,%5,%6,%7,%8,%9,%10,%11,%12,%13,%14,%15,%16,%17,%18,%19,"
        "%20,%21,%22,%23,%24,%25,%26,%27,%28,%29,%30,%31,%32,%33,%34,%35,%36,%37,%38,%39,"
        "%40,%41,%42,%43,%44,%45,%46,%47,%48,%49,%50,%51,%52,%53,%54,%55}, "
        "%56, %57, p, 1, 1, 0, 1;\n}\n"
        : "+f"(d[0]), "+f"(d[1]), "+f"(d[2]), "+f"(d[3]), "+f"(d[4]), "+f"(d[5]), "+f"(d[6]), "+f"(d[7]), "+f"(d[8]), "+f"(d[9]),
          "+f"(d[10]), "+f"(d[11]), "+f"(d[12]), "+f"(d[13]), "+f"(d[14]), "+f"(d[15]), "+f"(d[16]), "+f"(d[17]), "+f"(d[18]), "+f"(d[19]),
          "+f"(d[20]), "+f"(d[21]), "+f"(d[22]), "+f"(d[23]), "+f"(d[24]), "+f"(d[25]), "+f"(d[26]), "+f"(d[27]), "+f"(d[28]), "+f"(d[29]),
          "+f"(d[30]), "+f"(d[31]), "+f"(d[32]), "+f"(d[33]), "+f"(d[34]), "+f"(d[35]), "+f"(d[36]), "+f"(d[37]), "+f"(d[38]), "+f"(d[39]),
          "+f"(d[40]), "+f"(d[41]), "+f"(d[42]), "+f"(d[43]), "+f"(d[44]), "+f"(d[45]), "+f"(d[46]), "+f"(d[47]), "+f"(d[48]), "+f"(d[49]),
          "+f"(d[50]), "+f"(d[51]), "+f"(d[52]), "+f"(d[53]), "+f"(d[54]), "+f"(d[55])
        : "l"(da), "l"(db));
}
__device__ __forceinline__ void wgmma_rs80(float (&d)[40], uint32_t a0, uint32_t a1, uint32_t a2, uint32_t a3, uint64_t db) {
    asm volatile("{\n.reg .pred p;\nsetp.eq.b32 p, 0, 0;\n"
        "wgmma.mma_async.sync.aligned.m64n80k16.f32.bf16.bf16 "
        "{%0,%1,%2,%3,%4,%5,%6,%7,%8,%9,%10,%11,%12,%13,%14,%15,%16,%17,%18,%19,"
        "%20,%21,%22,%23,%24,%25,%26,%27,%28,%29,%30,%31,%32,%33,%34,%35,%36,%37,%38,%39}, "
        "{%40,%41,%42,%43}, %44, p, 1, 1, 1;\n}\n"
        : "+f"(d[0]), "+f"(d[1]), "+f"(d[2]), "+f"(d[3]), "+f"(d[4]), "+f"(d[5]), "+f"(d[6]), "+f"(d[7]), "+f"(d[8]), "+f"(d[9]),
          "+f"(d[10]), "+f"(d[11]), "+f"(d[12]), "+f"(d[13]), "+f"(d[14]), "+f"(d[15]), "+f"(d[16]), "+f"(d[17]), "+f"(d[18]), "+f"(d[19]),
          "+f"(d[20]), "+f"(d[21]), "+f"(d[22]), "+f"(d[23]), "+f"(d[24]), "+f"(d[25]), "+f"(d[26]), "+f"(d[27]), "+f"(d[28]), "+f"(d[29]),
          "+f"(d[30]), "+f"(d[31]), "+f"(d[32]), "+f"(d[33]), "+f"(d[34]), "+f"(d[35]), "+f"(d[36]), "+f"(d[37]), "+f"(d[38]), "+f"(d[39])
        : "r"(a0), "r"(a1), "r"(a2), "r"(a3), "l"(db));
}
__device__ __forceinline__ void wgmma_qk0(float (&d)[32], uint32_t a0, uint32_t a1, uint32_t a2, uint32_t a3, uint64_t db) {
    asm volatile("{\n.reg .pred p;\nsetp.ne.b32 p, 0, 0;\n"
        "wgmma.mma_async.sync.aligned.m64n64k16.f32.bf16.bf16 "
        "{%0,%1,%2,%3,%4,%5,%6,%7,%8,%9,%10,%11,%12,%13,%14,%15,%16,%17,%18,%19,"
        "%20,%21,%22,%23,%24,%25,%26,%27,%28,%29,%30,%31}, "
        "{%32,%33,%34,%35}, %36, p, 1, 1, 0;\n}\n"
        : "=f"(d[0]), "=f"(d[1]), "=f"(d[2]), "=f"(d[3]), "=f"(d[4]), "=f"(d[5]), "=f"(d[6]), "=f"(d[7]), "=f"(d[8]), "=f"(d[9]),
          "=f"(d[10]), "=f"(d[11]), "=f"(d[12]), "=f"(d[13]), "=f"(d[14]), "=f"(d[15]), "=f"(d[16]), "=f"(d[17]), "=f"(d[18]), "=f"(d[19]),
          "=f"(d[20]), "=f"(d[21]), "=f"(d[22]), "=f"(d[23]), "=f"(d[24]), "=f"(d[25]), "=f"(d[26]), "=f"(d[27]), "=f"(d[28]), "=f"(d[29]),
          "=f"(d[30]), "=f"(d[31])
        : "r"(a0), "r"(a1), "r"(a2), "r"(a3), "l"(db));
}
__device__ __forceinline__ void wgmma_qk1(float (&d)[32], uint32_t a0, uint32_t a1, uint32_t a2, uint32_t a3, uint64_t db) {
    asm volatile("{\n.reg .pred p;\nsetp.eq.b32 p, 0, 0;\n"
        "wgmma.mma_async.sync.aligned.m64n64k16.f32.bf16.bf16 "
        "{%0,%1,%2,%3,%4,%5,%6,%7,%8,%9,%10,%11,%12,%13,%14,%15,%16,%17,%18,%19,"
        "%20,%21,%22,%23,%24,%25,%26,%27,%28,%29,%30,%31}, "
        "{%32,%33,%34,%35}, %36, p, 1, 1, 0;\n}\n"
        : "+f"(d[0]), "+f"(d[1]), "+f"(d[2]), "+f"(d[3]), "+f"(d[4]), "+f"(d[5]), "+f"(d[6]), "+f"(d[7]), "+f"(d[8]), "+f"(d[9]),
          "+f"(d[10]), "+f"(d[11]), "+f"(d[12]), "+f"(d[13]), "+f"(d[14]), "+f"(d[15]), "+f"(d[16]), "+f"(d[17]), "+f"(d[18]), "+f"(d[19]),
          "+f"(d[20]), "+f"(d[21]), "+f"(d[22]), "+f"(d[23]), "+f"(d[24]), "+f"(d[25]), "+f"(d[26]), "+f"(d[27]), "+f"(d[28]), "+f"(d[29]),
          "+f"(d[30]), "+f"(d[31])
        : "r"(a0), "r"(a1), "r"(a2), "r"(a3), "l"(db));
}
__device__ __forceinline__ void wgmma_pv(float (&d)[12], uint32_t a0, uint32_t a1, uint32_t a2, uint32_t a3, uint64_t db) {
    asm volatile("{\n.reg .pred p;\nsetp.eq.b32 p, 0, 0;\n"
        "wgmma.mma_async.sync.aligned.m64n24k16.f32.bf16.bf16 "
        "{%0,%1,%2,%3,%4,%5,%6,%7,%8,%9,%10,%11}, "
        "{%12,%13,%14,%15}, %16, p, 1, 1, 1;\n}\n"
        : "+f"(d[0]), "+f"(d[1]), "+f"(d[2]), "+f"(d[3]), "+f"(d[4]), "+f"(d[5]), "+f"(d[6]), "+f"(d[7]), "+f"(d[8]), "+f"(d[9]),
          "+f"(d[10]), "+f"(d[11])
        : "r"(a0), "r"(a1), "r"(a2), "r"(a3), "l"(db));
}
__device__ __forceinline__ void wgmma_pv0(float (&d)[12], uint32_t a0, uint32_t a1, uint32_t a2, uint32_t a3, uint64_t db) {
    asm volatile("{\n.reg .pred p;\nsetp.ne.b32 p, 0, 0;\n"
        "wgmma.mma_async.sync.aligned.m64n24k16.f32.bf16.bf16 "
        "{%0,%1,%2,%3,%4,%5,%6,%7,%8,%9,%10,%11}, "
        "{%12,%13,%14,%15}, %16, p, 1, 1, 1;\n}\n"
        : "=f"(d[0]), "=f"(d[1]), "=f"(d[2]), "=f"(d[3]), "=f"(d[4]), "=f"(d[5]), "=f"(d[6]), "=f"(d[7]), "=f"(d[8]), "=f"(d[9]),
          "=f"(d[10]), "=f"(d[11])
        : "r"(a0), "r"(a1), "r"(a2), "r"(a3), "l"(db));
}
__device__ __forceinline__ void wgmma_l64a(float (&d)[32], uint64_t da, uint64_t db) {
    asm volatile("{\n.reg .pred p;\nsetp.ne.b32 p, 0, 0;\n"
        "wgmma.mma_async.sync.aligned.m64n64k16.f32.bf16.bf16 "
        "{%0,%1,%2,%3,%4,%5,%6,%7,%8,%9,%10,%11,%12,%13,%14,%15,%16,%17,%18,%19,"
        "%20,%21,%22,%23,%24,%25,%26,%27,%28,%29,%30,%31}, "
        "%32, %33, p, 1, 1, 0, 0;\n}\n"
        : "=f"(d[0]), "=f"(d[1]), "=f"(d[2]), "=f"(d[3]), "=f"(d[4]), "=f"(d[5]), "=f"(d[6]), "=f"(d[7]), "=f"(d[8]), "=f"(d[9]),
          "=f"(d[10]), "=f"(d[11]), "=f"(d[12]), "=f"(d[13]), "=f"(d[14]), "=f"(d[15]), "=f"(d[16]), "=f"(d[17]), "=f"(d[18]), "=f"(d[19]),
          "=f"(d[20]), "=f"(d[21]), "=f"(d[22]), "=f"(d[23]), "=f"(d[24]), "=f"(d[25]), "=f"(d[26]), "=f"(d[27]), "=f"(d[28]), "=f"(d[29]),
          "=f"(d[30]), "=f"(d[31])
        : "l"(da), "l"(db));
}
__device__ __forceinline__ void wgmma_l64b(float (&d)[32], uint64_t da, uint64_t db) {
    asm volatile("{\n.reg .pred p;\nsetp.eq.b32 p, 0, 0;\n"
        "wgmma.mma_async.sync.aligned.m64n64k16.f32.bf16.bf16 "
        "{%0,%1,%2,%3,%4,%5,%6,%7,%8,%9,%10,%11,%12,%13,%14,%15,%16,%17,%18,%19,"
        "%20,%21,%22,%23,%24,%25,%26,%27,%28,%29,%30,%31}, "
        "%32, %33, p, 1, 1, 0, 0;\n}\n"
        : "+f"(d[0]), "+f"(d[1]), "+f"(d[2]), "+f"(d[3]), "+f"(d[4]), "+f"(d[5]), "+f"(d[6]), "+f"(d[7]), "+f"(d[8]), "+f"(d[9]),
          "+f"(d[10]), "+f"(d[11]), "+f"(d[12]), "+f"(d[13]), "+f"(d[14]), "+f"(d[15]), "+f"(d[16]), "+f"(d[17]), "+f"(d[18]), "+f"(d[19]),
          "+f"(d[20]), "+f"(d[21]), "+f"(d[22]), "+f"(d[23]), "+f"(d[24]), "+f"(d[25]), "+f"(d[26]), "+f"(d[27]), "+f"(d[28]), "+f"(d[29]),
          "+f"(d[30]), "+f"(d[31])
        : "l"(da), "l"(db));
}
__device__ __forceinline__ void wgmma_l16a(float (&d)[8], uint64_t da, uint64_t db) {
    asm volatile("{\n.reg .pred p;\nsetp.ne.b32 p, 0, 0;\n"
        "wgmma.mma_async.sync.aligned.m64n16k16.f32.bf16.bf16 "
        "{%0,%1,%2,%3,%4,%5,%6,%7}, "
        "%8, %9, p, 1, 1, 0, 0;\n}\n"
        : "=f"(d[0]), "=f"(d[1]), "=f"(d[2]), "=f"(d[3]), "=f"(d[4]), "=f"(d[5]), "=f"(d[6]), "=f"(d[7])
        : "l"(da), "l"(db));
}
__device__ __forceinline__ void wgmma_l16b(float (&d)[8], uint64_t da, uint64_t db) {
    asm volatile("{\n.reg .pred p;\nsetp.eq.b32 p, 0, 0;\n"
        "wgmma.mma_async.sync.aligned.m64n16k16.f32.bf16.bf16 "
        "{%0,%1,%2,%3,%4,%5,%6,%7}, "
        "%8, %9, p, 1, 1, 0, 0;\n}\n"
        : "+f"(d[0]), "+f"(d[1]), "+f"(d[2]), "+f"(d[3]), "+f"(d[4]), "+f"(d[5]), "+f"(d[6]), "+f"(d[7])
        : "l"(da), "l"(db));
}

__device__ __forceinline__ uint32_t exp2_pair_fma(float a, float b) {
    const uint32_t y = __byte_perm(__float_as_uint(a), __float_as_uint(b), 0x6521);
    const uint32_t z = 0xFE7BFE7Bu - y;
    const uint32_t e = hfma2(y, z, 0x3F053F05u);
    return hfma2(y, e, y);
}
template <int MASK> __device__ __forceinline__ void exp_tile(const float (&s)[32], uint32_t (&p)[16]) {
#pragma unroll
    for (int j = 0; j < 8; j++) {
        if ((MASK >> j) & 1) { p[2 * j] = exp2_pair_fma(s[4 * j], s[4 * j + 1]); p[2 * j + 1] = exp2_pair_fma(s[4 * j + 2], s[4 * j + 3]); }
        else { p[2 * j] = pack2(ex2(s[4 * j]), ex2(s[4 * j + 1])); p[2 * j + 1] = pack2(ex2(s[4 * j + 2]), ex2(s[4 * j + 3])); }
    }
}
__device__ __forceinline__ void qk_tile(float (&s)[32], const uint32_t (&q)[8], uint64_t dk0, uint64_t dk1) {
    wgmma_qk0(s, q[0], q[1], q[2], q[3], dk0);
    wgmma_qk1(s, q[4], q[5], q[6], q[7], dk1);
}
__device__ __forceinline__ void pv_tile(float (&o)[12], const uint32_t (&p)[16], uint64_t dv) {
#pragma unroll
    for (int k = 0; k < 4; k++) wgmma_pv(o, p[4 * k], p[4 * k + 1], p[4 * k + 2], p[4 * k + 3], dv + k * 48);
}
__device__ __forceinline__ void finish_o(const float (&o)[12], uint32_t (&w)[6], int odd, float g0, float g1, int lane, float& l0, float& l1) {
    const int src = (lane & ~3) | (odd ? 0 : 2);
    l0 = __shfl_sync(0xffffffffu, o[8], src);
    l1 = __shfl_sync(0xffffffffu, o[10], src);
    float r0, r1;
    asm("rcp.approx.ftz.f32 %0, %1;" : "=f"(r0) : "f"(l0));
    asm("rcp.approx.ftz.f32 %0, %1;" : "=f"(r1) : "f"(l1));
    const float f0 = g0 * r0, f1 = g1 * r1;
#pragma unroll
    for (int d = 0; d < 3; d++) { w[2 * d] = pack2(o[4 * d] * f0, o[4 * d + 1] * f0); w[2 * d + 1] = pack2(o[4 * d + 2] * f1, o[4 * d + 3] * f1); }
}
__device__ __forceinline__ void stage_o(const uint32_t (&w)[6], uint32_t stg, int blk4, int lane, int odd) {
    const int pos = frag_pos(blk4, lane);
    const uint32_t a = stg + (odd ? 512 : 0) + pos * 8;
    sts64(a, w[0], w[1]);
    sts64(a + 1024, w[2], w[3]);
    if (((lane & 3) >= 2) == (odd != 0)) sts64(stg + (odd ? 0 : 2048) + (pos & 63) * 8, w[4], w[5]);
}
__device__ __forceinline__ bool store_piece(const uint32_t (&w)[6], uint32_t sO, int mt64, int h, int gbase, int tid, bool p) {
    const int odd = h & 1, lane = tid & 31, wg = tid >> 7;
    const uint32_t stg = sO + wg * 2560;
    stage_o(w, stg, (tid >> 5) & 3, lane, odd);
    fence_async_smem();
    const bool r = named_sync_or(8 + wg, 128, p);
    if ((tid & 127) == 0) {
        bulk_s2g(g_att + (mt64 * 160 + gbase) * 128 + h * 320, stg, 2560);
        bulk_commit();
    }
    return r;
}

#define PACE 300u
#define PROMO CU_TENSOR_MAP_L2_PROMOTION_L2_256B
#define WOD 500
#define MAP 1
#define P1_NT(b) ((b) >> 4)
#define P1_MP(b) (((b) >> 1) & 7)
#define LJ 16
#define LJ2 20
#define DEFER 4
constexpr int SLOT = 24576;
constexpr int OFF_X = 98304, OFF_R = 6 * SLOT, OFF_L = OFF_R - 1536, OFF_BAR = 9 * SLOT, OFF_O = OFF_BAR + 1024;
constexpr int SMEM_BYTES = OFF_O + 4 * 2560;
enum { B_FULL = 0, B_EMPTY = 48, B_STGB = 96, B_STGA = 104, B_RET = 112, B_NRM = 144, B_HLP = 152, B_KV = 160, B_HDR = 192, B_L = 200, B_WO = 208, B_FA = 232, B_FB = 240, B_XCH = 248, B_LD = 264, B_ZERO = 272, B_MISC = 288 };
__host__ __device__ constexpr int k_off(int j) {
    return j < 8 ? (7 + (j >> 2)) * SLOT + (j & 3) * 3072 : j == 8 ? OFF_R - 6144 : j < 20 ? 3 * SLOT + (j - 9) * 3072 : (j - 20) * 3072;
}
__host__ __device__ constexpr int v_off(int j) { return k_off(j) + (j < 8 ? 4 : j == 8 ? 1 : j < 20 ? 11 : 12) * 3072; }
__host__ __device__ constexpr int wo_off(int i) { return i < 7 ? 3 * SLOT + i * 20480 : (i - 7) * 20480; }
__host__ __device__ constexpr int wo_bar(int i) { return i < 3 ? 0 : i < 7 ? 1 : 2; }
constexpr float SCORE_LIMIT2 = 118.f * 118.f;

__device__ __forceinline__ void load_kv(uint32_t sb, int h, int i, int j0, int n, int arm) {
    const uint32_t bar = sb + OFF_BAR + B_KV + 8 * i;
    if (arm) mbar_expect_tx(bar, arm * 6144);
    bulk_g2s(sb + k_off(j0), g_qkv + (size_t)(32 + h) * HEAD_BYTES + j0 * 3072, n * 3072, bar);
    bulk_g2s(sb + v_off(j0), g_qkv + (size_t)(64 + h) * HEAD_BYTES + j0 * 3072, n * 3072, bar);
}
__device__ __forceinline__ void load_wo(uint32_t sb, int seq, int n) {
    const uint32_t bar = sb + OFF_BAR + B_WO + 8 * wo_bar(seq);
    mbar_expect_tx(bar, n * 20480);
    bulk_g2s(sb + wo_off(seq), reinterpret_cast<const uint8_t*>(g_wo) + (blockIdx.x & 7) * 204800 + seq * 20480, n * 20480, bar);
}

__device__ __forceinline__ void local_attn(uint32_t sb) {
    const uint32_t sL = sb + OFF_L, sO = sb + OFF_O;
    const int tid = fresh_tid(), lane = tid & 31, g = lane >> 2, t = lane & 3;
    const int wg = __shfl_sync(0xffffffffu, tid >> 7, 0), w = (tid >> 5) & 3;
    const int bid = fresh_bid(), h = bid >> 2, qb = bid & 3, odd = h & 1;
    const float* gp = g_gate + qb * 512 + wg * 128 + w * 16 + g;
    const float gt[4] = {ldcg_f32(gp), ldcg_f32(gp + 8), ldcg_f32(gp + 64), ldcg_f32(gp + 72)};
    TR2(40, tid == 64);
    const bool godd = g & 1;
    const bool early = 2 * t > (g & 6);
    if ((tid & 127) == 0) bulk_wait_read();
    mbar_wait(sb + OFF_BAR + B_L, 0);
    TR2(41, tid == 64);
    float va[4], vb[4];
    {
        const uint32_t tq = sL + wg * 6144;
        const uint64_t dq0 = mkdesc(tq, 128, 384, 0), dq1 = mkdesc(tq + 256, 0, 384, 0);
        float sa[2][32], sc[2][8];
        wg_fence();
#pragma unroll
        for (int b = 0; b < 2; b++) {
            wgmma_l64a(sa[b], dq0 + b * 192, dq0 + b * 192 + (24576 >> 4)); wgmma_l64b(sa[b], dq1 + b * 192, dq1 + b * 192 + (24576 >> 4));
            wgmma_l16a(sc[b], dq0 + b * 192, dq0 + b * 192 + (27648 >> 4)); wgmma_l16b(sc[b], dq1 + b * 192, dq1 + b * 192 + (27648 >> 4));
        }
        wg_commit(); wg_wait<0>(); pin(sa[0]); pin(sa[1]); pin(sc[0]); pin(sc[1]);
        TR2(42, tid == 64);
#define LSEL(B, W, I, R) (godd ? ((W) * 2 + (I) < 8 ? sa[B][(((W) * 2 + (I)) * 4 + 2 * (R) + 1) & 31] : sc[B][(((W) * 2 + (I)) * 4 + 2 * (R) + 1) & 7]) \
                               : ((W) * 2 + (I) < 8 ? sa[B][(((W) * 2 + (I)) * 4 + 2 * (R)) & 31] : sc[B][(((W) * 2 + (I)) * 4 + 2 * (R)) & 7]))
#define LWIN(W) { _Pragma("unroll") for (int i = 0; i < 4; i++) { va[i] = LSEL(i >> 1, W, 1 + (i & 1), i & 1); \
                  vb[i] = early ? LSEL(i >> 1, W, i & 1, i & 1) : LSEL(i >> 1, W, 2 + (i & 1), i & 1); } }
        if (w == 0) LWIN(0) else if (w == 1) LWIN(1) else if (w == 2) LWIN(2) else LWIN(3)
#undef LWIN
#undef LSEL
    }
    if (qb == 0 && tid < 32) {
        va[0] = -INFINITY;
        if (early) vb[0] = vb[1] = -INFINITY;
    }
    float m[4];
#pragma unroll
    for (int i = 0; i < 4; i++) m[i] = fmaxf(va[i], vb[i]);
#pragma unroll
    for (int i = 0; i < 4; i++) m[i] = fmaxf(m[i], __shfl_xor_sync(0xffffffffu, m[i], 1));
#pragma unroll
    for (int i = 0; i < 4; i++) m[i] = fmaxf(m[i], __shfl_xor_sync(0xffffffffu, m[i], 2));
    const uint32_t sel_a = godd ? 0x1044u : 0x4410u, sel_b = godd ? 0x3244u : 0x4432u;
    const int e = w + (early ? 0 : 1);
    uint32_t p[2][20];
#pragma unroll
    for (int b = 0; b < 2; b++) {
        const uint32_t pp0 = pack2(ex2(va[2 * b] - m[2 * b]), ex2(vb[2 * b] - m[2 * b]));
        const uint32_t pp1 = pack2(ex2(va[2 * b + 1] - m[2 * b + 1]), ex2(vb[2 * b + 1] - m[2 * b + 1]));
        const uint32_t pa0 = __byte_perm(pp0, 0u, sel_a), pa1 = __byte_perm(pp1, 0u, sel_a);
        const uint32_t pb0 = __byte_perm(pp0, 0u, sel_b), pb1 = __byte_perm(pp1, 0u, sel_b);
#pragma unroll
        for (int ks = 0; ks < 5; ks++) {
            p[b][4 * ks] = ks == e ? pb0 : 0u; p[b][4 * ks + 1] = ks == w + 1 ? pa1 : 0u;
            p[b][4 * ks + 2] = ks == w ? pa0 : 0u; p[b][4 * ks + 3] = ks == e ? pb1 : 0u;
        }
    }
    pin(p[0]); pin(p[1]);
    TR2(44, tid == 64);
    const uint64_t dv = mkdesc(sL + 24576 + 25344 + wg * 6144, 384, 128, 0);
    float o[2][12];
    wg_fence();
#pragma unroll
    for (int b = 0; b < 2; b++) {
        wgmma_pv0(o[b], p[b][0], p[b][1], p[b][2], p[b][3], dv + b * 192);
#pragma unroll
        for (int ks = 1; ks < 5; ks++) wgmma_pv(o[b], p[b][4 * ks], p[b][4 * ks + 1], p[b][4 * ks + 2], p[b][4 * ks + 3], dv + b * 192 + ks * 48);
    }
    wg_commit();
    named_sync(8 + wg, 128);
    wg_wait<0>(); pin(o[0]); pin(o[1]);
    TR2(45, tid == 64);
#pragma unroll
    for (int b = 0; b < 2; b++) {
        float l0, l1;
        uint32_t wv[6];
        finish_o(o[b], wv, odd, gt[2 * b], gt[2 * b + 1], lane, l0, l1);
        stage_o(wv, b ? sL + wg * 6144 : sO + wg * 2560, w, lane, odd);
    }
    TR2(47, tid == 64);
    fence_async_smem();
    named_sync(8 + wg, 128);
    TR2(54, tid == 64);
    if ((tid & 127) == 0) {
        uint2* dst = g_att + (qb * 8 + wg * 2) * 160 * 128 + h * 320;
        bulk_s2g(dst, sO + wg * 2560, 2560);
        bulk_s2g(dst + 160 * 128, sL + wg * 6144, 2560);
        bulk_commit();
        TR2(7, tid == 0);
    }
    __syncwarp();
}

__device__ __noinline__ void exact_rows(int h, int row16, int lane) {
    const bool aug_lane = ((lane & 3) >= 2) != ((h & 1) != 0);
    const uint8_t* a = g_qkv + (size_t)h * HEAD_BYTES + row16 * 768 + lane * 4;
    const uint8_t* gk = g_qkv + (size_t)(32 + h) * HEAD_BYTES + lane * 4;
    const uint8_t* gv = g_qkv + (size_t)(64 + h) * HEAD_BYTES + lane * 4;
    const uint32_t q0 = ldcg_u32(a), q1 = ldcg_u32(a + 384), q2 = ldcg_u32(a + 128), q3 = ldcg_u32(a + 512);
    const uint32_t q4 = aug_lane ? 0u : ldcg_u32(a + 256), q5 = aug_lane ? 0u : ldcg_u32(a + 640);
    float m0 = -INFINITY, m1 = -INFINITY;
#pragma unroll 4
    for (int kg = 0; kg < 256; kg++) {
        const uint8_t* ka = gk + kg * 384;
        float c[4] = {0.f, 0.f, 0.f, 0.f};
        mma16816(c, q0, q1, q2, q3, ldcg_u32(ka), ldcg_u32(ka + 128));
        mma1688(c, q4, q5, ldcg_u32(ka + 256));
        m0 = fmaxf(m0, fmaxf(c[0], c[1])); m1 = fmaxf(m1, fmaxf(c[2], c[3]));
    }
    m0 = fmaxf(m0, __shfl_xor_sync(0xffffffffu, m0, 1)); m1 = fmaxf(m1, __shfl_xor_sync(0xffffffffu, m1, 1));
    m0 = fmaxf(m0, __shfl_xor_sync(0xffffffffu, m0, 2)); m1 = fmaxf(m1, __shfl_xor_sync(0xffffffffu, m1, 2));
    float oc[3][4];
#pragma unroll
    for (int d = 0; d < 3; d++) oc[d][0] = oc[d][1] = oc[d][2] = oc[d][3] = 0.f;
#pragma unroll 2
    for (int kg = 0; kg < 256; kg += 2) {
        uint32_t kk[2][3], vv[2][3], pp[2][2];
#pragma unroll
        for (int e = 0; e < 2; e++)
#pragma unroll
            for (int d = 0; d < 3; d++) { kk[e][d] = ldcg_u32(gk + (kg + e) * 384 + d * 128); vv[e][d] = ldcg_u32(gv + (kg + e) * 384 + d * 128); }
#pragma unroll
        for (int e = 0; e < 2; e++) {
            float c[4] = {0.f, 0.f, 0.f, 0.f};
            mma16816(c, q0, q1, q2, q3, kk[e][0], kk[e][1]);
            mma1688(c, q4, q5, kk[e][2]);
            const float f = ((POLY16 >> ((kg + e) & 15)) & 1) ? -2.f : 1.f;
            pp[e][0] = pack2(f * ex2(c[0] - m0), f * ex2(c[1] - m0));
            pp[e][1] = pack2(f * ex2(c[2] - m1), f * ex2(c[3] - m1));
        }
#pragma unroll
        for (int d = 0; d < 3; d++) mma16816(oc[d], pp[0][0], pp[0][1], pp[1][0], pp[1][1], movm_t(vv[0][d]), movm_t(vv[1][d]));
    }
    float o[12];
#pragma unroll
    for (int i = 0; i < 12; i++) o[i] = oc[i >> 2][i & 3];
    const int row = row16 * 16 + (lane >> 2);
    float l0, l1;
    uint32_t w[6];
    finish_o(o, w, h & 1, 1.f - ldcg_f32(g_gate + row), 1.f - ldcg_f32(g_gate + row + 8), lane, l0, l1);
    uint2* p = g_att + ((row16 >> 2) * 160 + 80 + 5 * (h >> 1)) * 128 + frag_pos(row16 & 3, lane);
    const int off = (h & 1) ? 3 * 128 : 0;
    stg64(p + off, w[0], w[1]);
    stg64(p + off + 128, w[2], w[3]);
    if (!aug_lane) stg64(p + 2 * 128, w[4], w[5]);
    __threadfence();
}

__device__ __forceinline__ bool first_unit_redo(const float* s_misc, int tid) {
    const float4 v = *reinterpret_cast<const float4*>(s_misc + (tid >> 7) * 4);
    return v.x + v.y + v.z + v.w + s_misc[16 + (tid >> 8)] != 0.f;
}
__device__ __noinline__ void service(uint32_t sb, int step) {
    const uint32_t bars = sb + OFF_BAR;
    const int bid = blockIdx.x, h = bid >> 2, qb = bid & 3;
    if (step == 0) {
        bulk_wait_all();
        flag_add_done(g_flag + (F_QKVA + P1_NT(bid)) * 32);
        load_kv(sb, h, 3, 20, 12, 12);
    } else if (step == 3) {
        mbar_wait(bars + B_RET + 24, 0);
        load_wo(sb, 0, 3);
    } else if (step == 2) {
        mbar_wait(bars + B_LD, 0);
        fence_async_smem();
        load_wo(sb, 3, 4);
    } else {
        mbar_wait(bars + B_RET, 0);
        fence_async_smem();
        const int halo = qb ? 768 : 0;
        const uint8_t* src = g_qkv + (size_t)(96 + h) * HEAD_BYTES + qb * 24576;
        mbar_expect_tx(bars + B_L, 3 * 24576 + 2 * halo);
        bulk_g2s(sb + OFF_L, src, 24576, bars + B_L);
        bulk_g2s(sb + OFF_L + 24576 + 768 - halo, src + (size_t)32 * HEAD_BYTES - halo, 24576 + halo, bars + B_L);
        bulk_g2s(sb + OFF_L + 24576 + 25344 + 768 - halo, src + (size_t)64 * HEAD_BYTES - halo, 24576 + halo, bars + B_L);
    }
}

__global__ void __cluster_dims__(2, 1, 1) __launch_bounds__(512, 1)
k_fused(const __grid_constant__ CUtensorMap tmX, const __grid_constant__ CUtensorMap tmWb, const __grid_constant__ CUtensorMap tmWa,
        const __grid_constant__ CUtensorMap tmS, const __nv_bfloat16* __restrict__ x, const __nv_bfloat16* __restrict__ gate_w,
        const uint8_t* __restrict__ wb, const uint8_t* __restrict__ wa, const uint8_t* __restrict__ woa, const uint8_t* __restrict__ wob,
        __nv_bfloat16* __restrict__ out) {
    extern __shared__ __align__(1024) uint8_t smem_raw[];
    const uint32_t sb = smem_u32(smem_raw);
    if (sb & 1023u) __trap();
    const uint32_t bars = sb + OFF_BAR;
    float* s_misc = reinterpret_cast<float*>(smem_raw + OFF_BAR + B_MISC);
    const int bid = blockIdx.x;
    const int h = bid >> 2, qb = bid & 3;

    {
        const int warp = __shfl_sync(0xffffffffu, threadIdx.x >> 5, 0), lane = threadIdx.x & 31;
        const int mt = P1_MP(bid) * 2 + (bid & 1), nt = P1_NT(bid);
        TRINIT(); TR(0, threadIdx.x == 0);
        if (threadIdx.x == 256) {
            prefetch_tmap(&tmX); prefetch_tmap(&tmWb);
#pragma unroll
            for (int i = 0; i < 6; i++) mbar_init(bars + B_FULL + 8 * i, 1);
            fence_mbar_init();
#pragma unroll
            for (int i = 0; i < 6; i++) mbar_expect_tx(bars + B_FULL + 8 * i, (i & 1) ? 16384 : 32768);
#pragma unroll
            for (int i = 0; i < 3; i++) tma_2d(sb + OFF_X + i * 16384, &tmX, i * 64, mt * 128, bars + B_FULL + 16 * i);
        } else if (threadIdx.x == 32) {
#pragma unroll
            for (int i = 0; i < 6; i++) mbar_init(bars + B_EMPTY + 8 * i, 16);
            fence_mbar_init();
        } else if (threadIdx.x == 64) {
            mbar_init(bars + B_STGB, 8); mbar_init(bars + B_STGA, 8);
            mbar_init(bars + B_RET, 16); mbar_init(bars + B_RET + 8, 8); mbar_init(bars + B_RET + 16, 16); mbar_init(bars + B_RET + 24, 16);
            mbar_init(bars + B_LD, 4); mbar_init(bars + B_NRM, 4); mbar_init(bars + B_HLP, 4);
            fence_mbar_init();
        } else if (threadIdx.x == 96) {
#pragma unroll
            for (int i = 0; i < 13; i++) mbar_init(bars + B_KV + 8 * i, 1);
            s_misc[-4] = 0.f; s_misc[-3] = 0.f;
            fence_mbar_init();
        }
        __syncwarp();
        cluster_arrive(); cluster_wait();

        if (warp < 8) {
            asm volatile("setmaxnreg.inc.sync.aligned.u32 152;");
            const int wg = warp >> 2, t = lane & 3;
            float acc0[64], acc1[56];
            int s = 0; uint32_t ph = 0;
#pragma unroll 1
            for (int br = 0; br < 2; br++) {
#pragma unroll
                for (int i = 0; i < 64; i++) acc0[i] = 0.f;
#pragma unroll
                for (int i = 0; i < 56; i++) acc1[i] = 0.f;
                pin(acc0); pin(acc1);
                int prev = -1;
#pragma unroll 1
                for (int kb = 0; kb < 20; kb++) {
                    const uint64_t db = mkdesc(sb + s * 16384, 4096, 1024, 1);
                    mbar_wait(bars + B_FULL + 8 * s, ph);
                    TR(1 + 3 * br, threadIdx.x == 0 && kb == 0);
                    const uint64_t da = mkdesc(sb + OFF_X + (s >> 1) * 16384 + wg * 8192 + (s & 1) * 64, 16, 1024, 1);
                    wg_fence();
#pragma unroll
                    for (int k = 0; k < 2; k++) {
                        wgmma_ss128(acc0, da + k * 2, db + k * 128);
                        wgmma_ss112(acc1, da + k * 2, db + k * 128 + 512);
                    }
                    wg_commit();
                    wg_wait<1>();
                    if (prev >= 0 && lane < 2) mbar_arrive_cluster(bars + B_EMPTY + 8 * prev, lane);
                    prev = s;
                    if (++s == 6) { s = 0; ph ^= 1; }
                }
                wg_wait<0>();
                pin(acc0); pin(acc1);
                if (lane < 2) mbar_arrive_cluster(bars + B_EMPTY + 8 * prev, lane);
                TR(2 + 3 * br, threadIdx.x == 0);
                if (br == 1) named_sync(1, 256);
                else mbar_wait(bars + B_HDR, 0);
                const uint32_t wst = sb + (br == 0 ? OFF_R : 0) + warp * 768 + (lane & 7) * 16;
                const uint32_t a0 = wst + (lane >> 3) * 128;
                const uint32_t a1 = wst + (lane < 16 ? 512 + (lane >> 3) * 128 : 6144 + ((lane >> 3) - 2) * 128);
                const uint32_t a2 = wst + 6144 + 256 + (lane >> 3) * 128;
#pragma unroll
                for (int u = 0; u < 6; u++) {
                    const int sec = (nt * 6 + u) >> 4;
                    uint32_t m[2][6];
#pragma unroll
                    for (int r = 0; r < 2; r++) {
                        const bool poly = (br == 0) && ((POLY16 >> ((warp * 2 + r) & 15)) & 1);
                        const float sc = sec == 0 ? QSCALE : (sec == 2 && poly) ? -0.5f : 1.f;
                        const float sc2 = (br == 1 && sec == 0) ? 0.5f * QSCALE : sc;
                        uint32_t aug;
                        if (sec == 0) aug = br == 0 ? 0x3D2D43C0u : 0u;
                        else if (sec == 1) aug = br == 0 ? (poly ? 0x00003F80u : 0x3F800000u) : 0u;
                        else aug = poly ? 0x0000BF00u : 0x00003F80u;
                        if (t & 1) aug = 0u;
                        uint32_t v[5];
#pragma unroll
                        for (int j = 0; j < 5; j++) {
                            const int i = (5 * u + j) * 4 + 2 * r;
                            const float f = j == 2 ? sc2 : sc;
                            v[j] = i < 64 ? pack2(acc0[i & 63] * f, acc0[(i + 1) & 63] * f) : pack2(acc1[(i - 64) % 56] * f, acc1[(i - 63) % 56] * f);
                        }
                        m[0][3 * r] = v[0]; m[0][3 * r + 1] = v[1]; m[0][3 * r + 2] = t < 2 ? v[2] : aug;
                        m[1][3 * r] = v[3]; m[1][3 * r + 1] = v[4]; m[1][3 * r + 2] = t < 2 ? aug : v[2];
                    }
                    stsm4(a0 + u * 12288, m[0][0], m[0][1], m[0][2], m[0][3]);
                    stsm4(a1 + u * 12288, m[0][4], m[0][5], m[1][0], m[1][1]);
                    stsm4(a2 + u * 12288, m[1][2], m[1][3], m[1][4], m[1][5]);
                }
                fence_async_smem();
                __syncwarp();
                if (lane == 0) mbar_arrive(bars + B_STGB + 8 * br);
                TR(3 + 3 * br, threadIdx.x == 0);
            }
            asm volatile("setmaxnreg.dec.sync.aligned.u32 128;");
        } else if (warp < 12) {
            asm volatile("setmaxnreg.dec.sync.aligned.u32 80;");
            if (warp == 8) {
                if (lane == 0) {
#pragma unroll 1
                    for (int rnd = 0; rnd < 7; rnd++) {
#pragma unroll
                        for (int s = 0; s < 6; s++) {
                            const int it = rnd * 6 + s;
                            if (it < 40) {
                                const int kb = it < 20 ? it : it < 26 ? it - 6 : it - 26;
                                const bool newx = it < 20 || it >= 26;
                                const CUtensorMap* tw = it >= 20 ? &tmWa : &tmWb;
                                const uint32_t st = sb + s * 16384 + (bid & 1) * 8192, fb = bars + B_FULL + 8 * s;
                                if (rnd) {
                                    mbar_wait(bars + B_EMPTY + 8 * s, (rnd & 1) ^ 1);
                                    mbar_expect_tx(fb, ((s & 1) || !newx) ? 16384 : 32768);
                                }
                                tma_3d_mc(st, tw, (bid & 1) * 128, nt, kb * 32, fb, 3);
                                tma_3d_mc(st + 4096, tw, (bid & 1) * 128 + 64, nt, kb * 32, fb, 3);
                                if ((s & 1) && rnd && newx) tma_2d(sb + OFF_X + (s >> 1) * 16384, &tmX, (kb - 1) * 32, mt * 128, fb - 8);
                            }
                        }
                        if (rnd == 2) { prefetch_tmap(&tmWa); prefetch_tmap(&tmS); l2_prefetch(wa + bid * 19200, 19200); }
                    }
                    mbar_wait(bars + B_KV, 0);
                    load_kv(sb, h, 1, 4, 4, 6);
                    bulk_g2s(sb + OFF_R + 12288, g_qkv + (size_t)h * HEAD_BYTES + qb * 24576 + 12288, 12288, bars + B_KV + 8);
                    mbar_wait(bars + B_EMPTY + 24, 0);
                    load_kv(sb, h, 2, 8, 1, 12); load_kv(sb, h, 2, 9, 11, 0);
                }
            } else if (warp == 9) {
                if (lane == 0) {
                    mbar_wait(bars + B_HLP, 0);
                    bulk_s2g(g_wo + bid * 800, sb + OFF_R, 12800);
                    bulk_s2g(g_gate + bid * 16, sb + OFF_R + 12800, 64);
                    bulk_commit();
                    bulk_wait_all();
                    mbar_arrive(bars + B_HDR);
                    flag_add_done(g_flag + F_HELP * 32);
                    TR2(53, true);
                    mbar_wait(bars + B_STGB, 0);
                    uint32_t tick = clock_lo();
#pragma unroll 1
                    for (int i = 0; i < 24; i++) {
                        while (clock_lo() - tick < PACE) {}
                        tick += PACE;
                        bulk_s2g(g_qkv + (size_t)(nt * 12 + (i >> 1)) * HEAD_BYTES + mt * 6144 + (i & 1) * 3072, sb + OFF_R + i * 3072, 3072);
                    }
                    mbar_wait(bars + B_NRM, 0);
                    bulk_s2g(g_nrm + mt * 96 + nt * 12, bars + B_MISC + 80, 48);
                    bulk_commit();
                    bulk_wait_all();
                    flag_add_done(g_flag + (F_QKVB + nt) * 32);
                    TR(8, true);
                    flag_wait_head(g_flag + F_QKVB * 32, h, 128);
                    fence_async_smem();
                    TR(9, true);
                    load_kv(sb, h, 0, 0, 4, 6);
                    bulk_g2s(sb + OFF_R, g_qkv + (size_t)h * HEAD_BYTES + qb * 24576, 12288, bars + B_KV);
                }
                __syncwarp();
                {
                    const uint32_t w = ldcg_u32(g_nrm + (lane < 16 ? lane * 96 + 32 + h : (qb * 4 + (lane & 3)) * 96 + h));
                    const float kn = __uint_as_float(__reduce_max_sync(0xffffffffu, lane < 16 ? w : 0u));
                    if (lane >= 16 && lane < 20) s_misc[lane] = __uint_as_float(w) * kn <= SCORE_LIMIT2 ? 0.f : 1.f;
                }
            }
            __syncwarp();
            named_sync(5, 128);
            asm volatile("setmaxnreg.inc.sync.aligned.u32 128;");
        } else {
            mbar_wait(bars + B_FULL, 0);
            {
                uint4 wv[7];
#pragma unroll
                for (int e = 0; e < 7; e++) {
                    const int i = threadIdx.x - 384 + e * 128, d = bid * 800 + i;
                    const int kr = d & 7, ng = (d >> 3) % 20, kg = (d / 160) % 80, part = bid >> 4;
                    const int k = ((kg >> 3) * 2 + (part & 1)) * 64 + (kg & 7) * 8 + kr;
                    const uint8_t* src = (k < 640 ? woa + k * 1280 : wob + (k - 640) * 1280) + ((part >> 1) * 20 + ng) * 16;
                    if (i < 800) wv[e] = __ldg(reinterpret_cast<const uint4*>(src));
                }
                const uint2* gw = reinterpret_cast<const uint2*>(gate_w) + lane;
                const uint2* xr = reinterpret_cast<const uint2*>(x + (size_t)(bid * 16 + (warp - 12) * 4) * DM) + lane;
                uint2 gv[5], xv[4][5];
#pragma unroll
                for (int i = 0; i < 5; i++) gv[i] = __ldg(gw + 32 * i);
#pragma unroll
                for (int i = 0; i < 20; i++) xv[i / 5][i % 5] = __ldg(xr + 32 * i);
                float a[4];
#pragma unroll
                for (int e = 0; e < 4; e++) {
                    a[e] = 0.f;
#pragma unroll
                    for (int i = 0; i < 5; i++) {
                        a[e] = fmaf(bf_lo(xv[e][i].x), bf_lo(gv[i].x), a[e]); a[e] = fmaf(bf_hi(xv[e][i].x), bf_hi(gv[i].x), a[e]);
                        a[e] = fmaf(bf_lo(xv[e][i].y), bf_lo(gv[i].y), a[e]); a[e] = fmaf(bf_hi(xv[e][i].y), bf_hi(gv[i].y), a[e]);
                    }
                }
#pragma unroll
                for (int o = 16; o; o >>= 1) {
#pragma unroll
                    for (int e = 0; e < 4; e++) a[e] += __shfl_xor_sync(0xffffffffu, a[e], o);
                }
                const float z = lane == 0 ? a[0] : lane == 1 ? a[1] : lane == 2 ? a[2] : a[3];
                if (lane < 4) asm volatile("st.shared.f32 [%0], %1;" ::"r"(sb + OFF_R + 12800 + ((warp - 12) * 4 + lane) * 4), "f"(__fdividef(1.f, 1.f + __expf(-z))) : "memory");
#pragma unroll
                for (int e = 0; e < 7; e++) {
                    const int i = threadIdx.x - 384 + e * 128;
                    if (i < 800) asm volatile("st.shared.v4.b32 [%0], {%1,%2,%3,%4};" ::"r"(sb + OFF_R + i * 16), "r"(wv[e].x), "r"(wv[e].y), "r"(wv[e].z), "r"(wv[e].w) : "memory");
                }
                fence_async_smem();
                __syncwarp();
                if (lane == 0) mbar_arrive(bars + B_HLP);
            }
            mbar_wait(bars + B_STGB, 0);
#pragma unroll 1
            for (int hs = warp - 12; hs < 12; hs += 4) {
                uint32_t nm = 0;
                if (nt * 12 + hs < 64) {
#pragma unroll
                    for (int i = 0; i < 4; i++) {
                        const uint32_t a = sb + OFF_R + hs * 6144 + (i * 4 + (lane >> 3)) * 384 + (lane & 7) * 16;
                        const uint4 k0 = lds128(a), k1 = lds128(a + 128);
                        uint32_t k2, k3;
                        asm volatile("ld.shared.v2.b32 {%0,%1}, [%2];" : "=r"(k2), "=r"(k3) : "r"(a + 256 + (hs & 1) * 8));
                        uint32_t n0 = hfma2(k2, k2, 0u), n1 = hfma2(k3, k3, 0u);
                        n0 = hfma2(k0.x, k0.x, n0); n1 = hfma2(k0.y, k0.y, n1); n0 = hfma2(k0.z, k0.z, n0); n1 = hfma2(k0.w, k0.w, n1);
                        n0 = hfma2(k1.x, k1.x, n0); n1 = hfma2(k1.y, k1.y, n1); n0 = hfma2(k1.z, k1.z, n0); n1 = hfma2(k1.w, k1.w, n1);
                        nm = max(nm, __float_as_uint((bf_lo(n0) + bf_hi(n0)) + (bf_lo(n1) + bf_hi(n1))));
                    }
                }
                nm = __reduce_max_sync(0xffffffffu, nm);
                if (lane == 0) s_misc[20 + hs] = __uint_as_float(nm) * 1.03f;
            }
            fence_async_smem();
            __syncwarp();
            if (lane == 0) mbar_arrive(bars + B_NRM);
        }
    }

    uint32_t aflag;
    {
        const uint64_t dK0 = mkdesc(sb, 128, 384, 0), dK1 = mkdesc(sb + 256, 0, 384, 0), dV = mkdesc(sb, 384, 128, 0);
        const bool lane0 = (threadIdx.x & 31) == 0;
        const int late = __shfl_sync(0xffffffffu, (threadIdx.x >> 7) & 2, 0);
        mbar_wait(bars + B_KV, 0);
        TR(10 + (threadIdx.x >> 7), (threadIdx.x & 127) == 0);
#pragma unroll 1
        for (int u = 0; u < 2; u++) {
            uint32_t q[8];
            {
                const int tid = fresh_tid(), lane = tid & 31, warp = tid >> 5;
                const uint32_t a = sb + OFF_R + (u * 32 + warp * 2) * 384 + lane * 4;
                q[0] = lds32(a); q[1] = lds32(a + 384); q[2] = lds32(a + 128); q[3] = lds32(a + 512);
                q[4] = lds32(a + 256); q[5] = lds32(a + 640);
                q[6] = lds32(bars + B_ZERO); q[7] = lds32(bars + B_ZERO + 4);
            }
            float o[12];
#pragma unroll
            for (int i = 0; i < 12; i++) o[i] = 0.f;
            pin(o); pin(q);
            float s0[32], s1[32];
            uint32_t p[16];
            float g0, g1;
            TR2(48 + u, fresh_tid() == 128);
            wg_fence(); qk_tile(s0, q, dK0 + (k_off(0) >> 4), dK1 + (k_off(0) >> 4)); wg_commit();
#pragma unroll
            for (int j = 0; j < 32; j += 2) {
                wg_fence(); qk_tile(s1, q, dK0 + (k_off(j + 1) >> 4), dK1 + (k_off(j + 1) >> 4)); wg_commit();
                wg_wait<1>(); pin(s0);
                exp_tile<POLY16 & 0xff>(s0, p);
                pin(p);
                wg_fence(); pv_tile(o, p, dV + (v_off(j) >> 4)); wg_commit();
                if (j + 2 < 32) {
                    TR(32 + u * 4 + j / 8, (j & 7) == 0 && fresh_tid() == 128);
                    if (j == 10) { if (u == 1 && lane0) mbar_arrive(bars + B_RET); }
                    if (j == 4) {
                        if (u == 0 && fresh_tid() == 448) {
                            const int bid = fresh_bid();
                            mbar_wait(bars + B_STGA, 0);
                            tma_store_3d(&tmS, sb, 0, (P1_MP(bid) * 2 + (bid & 1)) * 16, 96 + P1_NT(bid) * 12);
                            bulk_commit();
                        }
                        __syncwarp();
                    }
                    if (j == 12) { const int tid = fresh_tid(); if (tid == (u ? 160 : 448)) service(sb, u); __syncwarp(); }
                    if (j == 20) { if (u == 1 && lane0) mbar_arrive(bars + B_RET + 24); }
                    if (j == 24) { if (u == 1 && fresh_tid() == 448) service(sb, 3); __syncwarp(); }
                    if (j == LJ2 + 4) {
                        const int tid = fresh_tid();
                        if (u == 1 && (tid & 127) == 0) {
                            bulk_wait_all();
                            mbar_arrive(bars + B_LD);
                            if (!first_unit_redo(s_misc, tid)) flag_add_done(g_flag + (F_ATTA + (fresh_bid() & 3)) * 32);
                        }
                        __syncwarp();
                    }
                    if (j == LJ2 + 6) { if (u == 1 && fresh_tid() == 288) service(sb, 2); __syncwarp(); }
                    if (j == 28) {
                        const int tid = fresh_tid();
                        const float* gp = g_gate + qb * 512 + u * 256 + (tid >> 5) * 16 + ((tid & 31) >> 2);
                        g0 = ldcg_f32(gp); g1 = ldcg_f32(gp + 8);
                        aflag = ld_relaxed(g_flag + (F_ATTA + (fresh_bid() >> 5)) * 32);
                    }
                    if (j + 2 == 4) mbar_wait(bars + B_KV + 8, 0);
                    if (j + 2 == 8) mbar_wait(bars + B_KV + 16, 0);
                    if (j + 2 == 20) mbar_wait(bars + B_KV + 24, 0);
                }
                if (j + 2 < 32 && j != LJ && j != LJ2) {
                    wg_fence(); qk_tile(s0, q, dK0 + (k_off(j + 2) >> 4), dK1 + (k_off(j + 2) >> 4)); wg_commit();
                    wg_wait<1>();
                } else {
                    wg_wait<0>();
                }
                pin(s1);
                exp_tile<(POLY16 >> 8)>(s1, p);
                pin(p);
                wg_fence(); pv_tile(o, p, dV + (v_off(j + 1) >> 4)); wg_commit();
                if (j == LJ || j == LJ2) {
                    TR2(27, j == LJ && u == 1 && fresh_tid() == 64);
                    wg_wait<0>();
                    if (u + late == (j == LJ ? 1 : 3)) local_attn(sb);
                    wg_fence(); qk_tile(s0, q, dK0 + (k_off(j + 2) >> 4), dK1 + (k_off(j + 2) >> 4)); wg_commit();
                }
            }
            const int tid = fresh_tid(), lane = tid & 31, warp = tid >> 5;
            const int bid = fresh_bid(), h = bid >> 2, qb = bid & 3;
            TR2(50 + u, tid == 128);
            if (u == 0 && tid == 416)
                flag_wait_head(g_flag + F_QKVA * 32, h, 0);
            __syncwarp();
            wg_wait<0>(); pin(o);
            TR(14 + u * 4 + (tid >> 7), (tid & 127) == 0);
            if (u == 1) {
                if (lane == 0) mbar_arrive(bars + B_RET + 16);
                mbar_wait(bars + B_LD, 0);
            }
            TR2(55, u == 1 && tid == 64);
            float l0, l1;
            uint32_t w[6];
            finish_o(o, w, h & 1, 1.f - g0, 1.f - g1, lane, l0, l1);
            const float sum = (((o[0] + o[1]) + (o[2] + o[3])) + ((o[4] + o[5]) + (o[6] + o[7]))) + ((o[8] + o[9]) + (o[10] + o[11]));
            bool redo = __any_sync(0xffffffffu, !(l0 >= 9.3132257e-10f && l1 >= 9.3132257e-10f && fabsf(sum) <= 1e37f));
            bool redo0 = false;
            if (u == 0) { if (lane == 0) s_misc[warp] = redo ? 1.f : 0.f; }
            else { redo0 = s_misc[warp] + s_misc[16 + (warp >> 3)] != 0.f; redo |= s_misc[18 + (warp >> 3)] != 0.f; }
            TR2(56, u == 1 && tid == 64 && !redo);
            const bool any = store_piece(w, sb + OFF_O, qb * 8 + u * 4 + (warp >> 2), h, 80, tid, u == 1 && (redo || redo0));
            TR2(57, u == 1 && tid == 64);
            if (any) {
                if ((tid & 127) == 0) bulk_wait_all();
                named_sync(8 + (warp >> 2), 128);
                if (redo0) exact_rows(h, qb * 32 + warp, lane);
                if (redo) exact_rows(h, qb * 32 + 16 + warp, lane);
                named_sync(8 + (warp >> 2), 128);
                if ((tid & 127) == 0) { __threadfence(); if (first_unit_redo(s_misc, tid)) flag_add(g_flag + (F_ATTA + qb) * 32); }
            }
        }
    }

    {
        const int tid = fresh_tid(), lane = tid & 31;
        const int warp = __shfl_sync(0xffffffffu, tid >> 5, 0);
        const int bid = fresh_bid();
        if (warp >= 8) {
            asm volatile("setmaxnreg.dec.sync.aligned.u32 40;");
            if ((tid & 127) == 0) { bulk_wait_all(); flag_add_done(g_flag + (F_ATTB + (bid & 3)) * 32); }
            if (tid == 320) {
                mbar_expect_tx(bars + B_XCH, 20480); mbar_expect_tx(bars + B_XCH + 8, 20480);
                mbar_wait(bars + B_RET + 16, 0);
                __nanosleep(WOD);
                load_wo(sb, 7, 3);
            }
            if (tid == 288) {
                flag_wait(g_flag + (F_ATTA + (bid >> 5)) * 32, 128);
                mbar_arrive(bars + B_FA);
                flag_wait(g_flag + (F_ATTB + (bid >> 5)) * 32, 128);
                mbar_arrive(bars + B_FB);
                TR2(52, true);
                if (atomicAdd(g_flag + F_EXIT * 32, 1u) == 127u) {
#pragma unroll 1
                    for (int i = 0; i < F_COUNT; i++) g_flag[i * 32] = 0u;
                }
            }
        } else {
            const int mh = warp >> 2, rank = bid & 1;
            const int mt64 = (bid >> 5) * 8 + mh * 4 + ((bid >> 3) & 3);
            const uint2* ap = g_att + (mt64 * 160 + rank * 8) * 128 + frag_pos(warp & 3, lane);
            const uint64_t db = mkdesc(sb, 2560, 128, 0);
            TR(22, tid == 0);
            uint32_t a[6][16];
            auto load = [&](int i) {
#pragma unroll
                for (int j = 0; j < 8; j++)
                    asm volatile("ld.global.L1::no_allocate.v2.b32 {%0, %1}, [%2];" : "=r"(a[i % 6][2 * j]), "=r"(a[i % 6][2 * j + 1])
                                 : "l"(ap + (16 * i + j) * 128) : "memory");
            };
            const bool early = __all_sync(0xffffffffu, aflag >= 128);
            if (early) { asm volatile("fence.acquire.gpu;" ::: "memory"); load(0); }
            if ((tid & 127) == 0) { bulk_wait_all(); flag_add_done(g_flag + (F_ATTB + (bid & 3)) * 32); }
            __syncwarp();
            if (!early) { mbar_wait(bars + B_FA, 0); load(0); }
            asm volatile("setmaxnreg.inc.sync.aligned.u32 216;");
            load(1); load(2);
            float snd[40], keep[40];
#pragma unroll
            for (int i = 0; i < 40; i++) snd[i] = keep[i] = 0.f;
            pin(snd); pin(keep);
            const uint64_t dk = db + rank * 80, ds = db + (rank ^ 1) * 80;
            TR(23, tid == 0);
            auto half = [&](float (&acc)[40], uint64_t d, int i) {
#pragma unroll
                for (int k = 0; k < 4; k++)
                    wgmma_rs80(acc, a[i % 6][4 * k], a[i % 6][4 * k + 1], a[i % 6][4 * k + 2], a[i % 6][4 * k + 3], d + (wo_off(i) >> 4) + k * 320);
            };
            auto mma = [&](int i) {
                if (i == 0 || wo_bar(i) != wo_bar(i - 1)) mbar_wait(bars + B_WO + 8 * wo_bar(i), 0);
                pin(a[i % 6]);
                TR(24, tid == 0 && i == 0); TR2(61, tid == 192 && i == 0); TR2(62, tid == 192 && i == 4); TR2(63, tid == 192 && i == 5);
                wg_fence();
                half(snd, ds, i);
                if (i < 10 - DEFER) half(keep, dk, i);
                wg_commit();
            };
            auto loadp = [&](int i, int pred) {
#pragma unroll
                for (int j = 0; j < 8; j++)
                    asm volatile("{\n.reg .pred p;\nsetp.ne.u32 p, %3, 0;\n@p ld.global.L1::no_allocate.v2.b32 {%0, %1}, [%2];\n}\n"
                                 : "+r"(a[i % 6][2 * j]), "+r"(a[i % 6][2 * j + 1]) : "l"(ap + (16 * i + j) * 128), "r"(pred) : "memory");
            };
            mma(0); load(3); load(4);
#pragma unroll
            for (int j = 0; j < 16; j++) a[5][j] = 0u;
            loadp(5, mh == 0);
#pragma unroll
            for (int i = 1; i < 5; i++) { mma(i); wg_wait<1>(); if (i < 4) loadp(i + 5, mh == 0); }
            if (lane == 0) mbar_arrive_cluster(bars + B_RET + 8, rank ^ 1);
            if (mh) mbar_wait(bars + B_FB, 0);
            loadp(5, mh); loadp(6, mh); loadp(7, mh); loadp(8, mh); load(9);
#pragma unroll
            for (int i = 5; i < 10; i++) mma(i);
#pragma unroll
            for (int i = 10 - DEFER; i < 10; i++) half(keep, dk, i);
            wg_commit();
            const uint32_t xs = sb + wo_off(0) + tid * 16;
            {
                uint32_t ra, rb;
                asm volatile("mapa.shared::cluster.u32 %0, %1, %2;" : "=r"(ra) : "r"(xs), "r"(rank ^ 1));
                asm volatile("mapa.shared::cluster.u32 %0, %1, %2;" : "=r"(rb) : "r"(bars + B_XCH + 8 * mh), "r"(rank ^ 1));
                mbar_wait(bars + B_RET + 8, 0);
                wg_wait<1>();
                pin(snd);
#pragma unroll
                for (int j = 0; j < 10; j++)
                    asm volatile("st.async.weak.shared::cluster.mbarrier::complete_tx::bytes.v4.f32 [%0], {%1,%2,%3,%4}, [%5];"
                                 ::"r"(ra + j * 4096), "f"(snd[4 * j]), "f"(snd[4 * j + 1]), "f"(snd[4 * j + 2]), "f"(snd[4 * j + 3]), "r"(rb) : "memory");
            }
            wg_wait<0>();
            pin(keep);
            TR(25, tid == 0); TR2(60, tid == 192);
            mbar_wait(bars + B_XCH + 8 * mh, 0);
            TR2(58, tid == 192);
            uint32_t w[20];
#pragma unroll
            for (int j = 0; j < 10; j++) {
                const uint4 o = lds128(xs + j * 4096);
                w[2 * j] = pack2(keep[4 * j] + __uint_as_float(o.x), keep[4 * j + 1] + __uint_as_float(o.y));
                w[2 * j + 1] = pack2(keep[4 * j + 2] + __uint_as_float(o.z), keep[4 * j + 3] + __uint_as_float(o.w));
            }
            const uint32_t ot = sb + wo_off(2) + warp * 2816;
            const uint32_t sa = ot + (lane & 15) * 176 + (lane >> 4) * 16;
#pragma unroll
            for (int j = 0; j < 5; j++) stsm4(sa + j * 32, w[4 * j], w[4 * j + 1], w[4 * j + 2], w[4 * j + 3]);
            __syncwarp();
            __nv_bfloat16* ob = out + (size_t)(mt64 * 64 + (warp & 3) * 16) * DM + (bid & 7) * 80;
#pragma unroll
            for (int i = 0; i < 5; i++) {
                const int c = lane + 32 * i;
                stg128(ob + (c / 10) * DM + (c % 10) * 8, lds128(ot + (c / 10) * 176 + (c % 10) * 16));
            }
            TR(26, tid == 0); TR2(59, tid == 192);
            TRFLUSH();
        }
    }
}

typedef CUresult (*EncodeFn)(CUtensorMap*, CUtensorMapDataType, cuuint32_t, void*, const cuuint64_t*, const cuuint64_t*,
                             const cuuint32_t*, const cuuint32_t*, CUtensorMapInterleave, CUtensorMapSwizzle,
                             CUtensorMapL2promotion, CUtensorMapFloatOOBfill);

void make_map(EncodeFn fn, CUtensorMap* tm, const void* ptr, int rank, const cuuint64_t* dims, const cuuint64_t* strides,
              const cuuint32_t* box, CUtensorMapSwizzle swz) {
    const cuuint32_t es[4] = {1, 1, 1, 1};
    fn(tm, CU_TENSOR_MAP_DATA_TYPE_BFLOAT16, rank, const_cast<void*>(ptr), dims, strides, box, es, CU_TENSOR_MAP_INTERLEAVE_NONE,
       swz, PROMO, CU_TENSOR_MAP_FLOAT_OOB_FILL_NONE);
}

}

extern "C" void kernel_launch(void* const* d_in, const int* in_sizes, int n_in, void* d_out, int out_size) {
    (void)in_sizes; (void)n_in; (void)out_size;
    const __nv_bfloat16* x = (const __nv_bfloat16*)d_in[0];
    const __nv_bfloat16* wqkv_a = (const __nv_bfloat16*)d_in[1];
    const __nv_bfloat16* wo_a = (const __nv_bfloat16*)d_in[2];
    const __nv_bfloat16* wqkv_b = (const __nv_bfloat16*)d_in[4];
    const __nv_bfloat16* wo_b = (const __nv_bfloat16*)d_in[5];
    const __nv_bfloat16* gate_w = (const __nv_bfloat16*)d_in[6];

    void* fnp = nullptr;
    cudaDriverEntryPointQueryResult qr;
    cudaGetDriverEntryPoint("cuTensorMapEncodeTiled", &fnp, cudaEnableDefault, &qr);
    EncodeFn enc = (EncodeFn)fnp;
    void* qkv = nullptr;
    cudaGetSymbolAddress(&qkv, g_qkv);

    CUtensorMap tmX, tmWb, tmWa, tmS;
    {
        const cuuint64_t d[2] = {640, 2048}, s[1] = {1280};
        const cuuint32_t b[2] = {64, 128};
        make_map(enc, &tmX, x, 2, d, s, b, CU_TENSOR_MAP_SWIZZLE_128B);
    }
    {
        const cuuint64_t d[3] = {240, 8, 640}, s[2] = {480, 3840};
        const cuuint32_t b[3] = {64, 1, 32};
        make_map(enc, &tmWb, wqkv_b, 3, d, s, b, CU_TENSOR_MAP_SWIZZLE_128B);
        make_map(enc, &tmWa, wqkv_a, 3, d, s, b, CU_TENSOR_MAP_SWIZZLE_128B);
    }
    {
        const cuuint64_t d[3] = {192, 256, 192}, s[2] = {384, (cuuint64_t)HEAD_BYTES};
        const cuuint32_t b[3] = {192, 16, 12};
        make_map(enc, &tmS, qkv, 3, d, s, b, CU_TENSOR_MAP_SWIZZLE_NONE);
    }
    cudaFuncSetAttribute(k_fused, cudaFuncAttributeMaxDynamicSharedMemorySize, SMEM_BYTES);
    k_fused<<<128, 512, SMEM_BYTES, cudaStreamPerThread>>>(tmX, tmWb, tmWa, tmS, x, gate_w, (const uint8_t*)wqkv_b, (const uint8_t*)wqkv_a,
                                                          (const uint8_t*)wo_a, (const uint8_t*)wo_b, (__nv_bfloat16*)d_out);
}
```

```cpp
#include <cuda_runtime.h>
#include <cuda_bf16.h>
#include <cuda.h>
#include <stdint.h>

namespace {

constexpr int SEQ = 2048, DM = 640;
constexpr int HEAD_BYTES = 256 * 384;
#define POLYM 0xddddu
constexpr uint32_t POLY16 = POLYM;
constexpr float QSCALE = 0.22360679774997896f * 1.4426950408889634f;

__device__ __align__(1024) uint8_t g_qkv[2 * 96 * HEAD_BYTES];
__device__ __align__(128) float g_gate[SEQ];
__device__ __align__(128) float g_nrm[16 * 96];
enum { F_QKVB = 0, F_QKVA = 8, F_HELP = 16, F_EXIT = 17, F_ATTA = 18, F_ATTB = 26, F_COUNT = 58 };
__device__ uint32_t g_flag[F_COUNT * 32];
__device__ __align__(1024) uint4 g_wo[8 * 160 * 10 * 8];
__device__ __align__(1024) uint2 g_att[32 * 160 * 128];

#define TR(i, cond)
#define TRINIT()
#define TRFLUSH()
#define TR2(i, c) TR(i, c)
__device__ __forceinline__ uint32_t smem_u32(const void* p) { return (uint32_t)__cvta_generic_to_shared(p); }
__device__ __forceinline__ void mbar_init(uint32_t bar, int cnt) { asm volatile("mbarrier.init.shared::cta.b64 [%0], %1;" ::"r"(bar), "r"(cnt) : "memory"); }
__device__ __forceinline__ void mbar_expect_tx(uint32_t bar, int bytes) { asm volatile("mbarrier.arrive.expect_tx.shared::cta.b64 _, [%0], %1;" ::"r"(bar), "r"(bytes) : "memory"); }
__device__ __forceinline__ void mbar_arrive(uint32_t bar) { asm volatile("mbarrier.arrive.shared::cta.b64 _, [%0];" ::"r"(bar) : "memory"); }
__device__ __forceinline__ bool mbar_try(uint32_t bar, uint32_t parity) {
    uint32_t ok;
    asm volatile("{\n.reg .pred p;\nmbarrier.try_wait.parity.shared::cta.b64 p, [%1], %2;\nselp.u32 %0, 1, 0, p;\n}\n" : "=r"(ok) : "r"(bar), "r"(parity) : "memory");
    return ok;
}
__device__ __forceinline__ void mbar_wait(uint32_t bar, uint32_t parity) {
    if (mbar_try(bar, parity)) return;
#pragma unroll 1
    for (int i = 0; i < (1 << 21); i++)
        if (mbar_try(bar, parity)) return;
    __trap();
}
__device__ __forceinline__ void fence_mbar_init() { asm volatile("fence.mbarrier_init.release.cluster;" ::: "memory"); }
__device__ __forceinline__ void tma_x(uint32_t dst, const CUtensorMap* tm, int k, int blk16, uint32_t bar) {
    asm volatile("cp.async.bulk.tensor.4d.shared::cluster.global.mbarrier::complete_tx::bytes [%0], [%1, {%2, %5, %5, %3}], [%4];"
                 ::"r"(dst), "l"(tm), "r"(k), "r"(blk16), "r"(bar), "r"(0) : "memory");
}
__device__ __forceinline__ void tma_3d_mc(uint32_t dst, const CUtensorMap* tm, int c0, int c1, int c2, uint32_t bar, uint16_t mask) {
    asm volatile("cp.async.bulk.tensor.3d.shared::cluster.global.mbarrier::complete_tx::bytes.multicast::cluster [%0], [%1, {%2, %3, %4}], [%5], %6;"
                 ::"r"(dst), "l"(tm), "r"(c0), "r"(c1), "r"(c2), "r"(bar), "h"(mask) : "memory");
}
__device__ __forceinline__ void mbar_arrive_cluster(uint32_t bar, uint32_t cta) {
    asm volatile("{\n.reg .b32 ra;\nmapa.shared::cluster.u32 ra, %0, %1;\nmbarrier.arrive.shared::cluster.b64 _, [ra];\n}\n" ::"r"(bar), "r"(cta) : "memory");
}
__device__ __forceinline__ void tma_store_3d(const CUtensorMap* tm, uint32_t src, int c0, int c1, int c2) {
    asm volatile("cp.async.bulk.tensor.3d.global.shared::cta.bulk_group [%0, {%2, %3, %4}], [%1];" ::"l"(tm), "r"(src), "r"(c0), "r"(c1), "r"(c2) : "memory");
}
__device__ __forceinline__ void cluster_arrive() { asm volatile("barrier.cluster.arrive.relaxed.aligned;" ::: "memory"); }
__device__ __forceinline__ void cluster_wait() { asm volatile("barrier.cluster.wait.aligned;" ::: "memory"); }
__device__ __forceinline__ void named_sync(int id, int n) { asm volatile("bar.sync %0, %1;" ::"r"(id), "r"(n) : "memory"); }
__device__ __forceinline__ void flag_add_done(uint32_t* p) {
    asm volatile("fence.proxy.async.global;\nred.release.gpu.global.add.u32 [%0], 1;" ::"l"(p) : "memory");
}
__device__ __forceinline__ void flag_wait(const uint32_t* p, uint32_t target) {
#pragma unroll 1
    for (int i = 0; i < (1 << 22); i++) {
        uint32_t v;
        asm volatile("ld.acquire.gpu.global.u32 %0, [%1];" : "=r"(v) : "l"(p) : "memory");
        if (v >= target) return;
        __nanosleep(20);
    }
    __trap();
}
__device__ __forceinline__ void flag_wait_head(const uint32_t* base, int h, uint32_t help_target) {
    const uint32_t *p0 = base + (h / 12) * 32, *p1 = base + ((32 + h) / 12) * 32, *p2 = base + ((64 + h) / 12) * 32;
    const uint32_t target = 16;
#pragma unroll 1
    for (int i = 0; i < (1 << 22); i++) {
        uint32_t v0, v1, v2, v3;
        asm volatile("ld.relaxed.gpu.global.u32 %0, [%1];" : "=r"(v3) : "l"(g_flag + F_HELP * 32) : "memory");
        asm volatile("ld.relaxed.gpu.global.u32 %0, [%1];" : "=r"(v0) : "l"(p0) : "memory");
        asm volatile("ld.relaxed.gpu.global.u32 %0, [%1];" : "=r"(v1) : "l"(p1) : "memory");
        asm volatile("ld.relaxed.gpu.global.u32 %0, [%1];" : "=r"(v2) : "l"(p2) : "memory");
        if (v0 >= target && v1 >= target && v2 >= target && v3 >= help_target) { asm volatile("fence.acquire.gpu;" ::: "memory"); return; }
        __nanosleep(40);
    }
    __trap();
}
__device__ __forceinline__ uint32_t ld_relaxed(const uint32_t* p) { uint32_t v; asm volatile("ld.relaxed.gpu.global.u32 %0, [%1];" : "=r"(v) : "l"(p) : "memory"); return v; }
__device__ __forceinline__ float ldcg_f32(const float* p) { float v; asm volatile("ld.global.cg.f32 %0, [%1];" : "=f"(v) : "l"(p) : "memory"); return v; }
__device__ __forceinline__ uint32_t ldcg_u32(const void* p) { uint32_t v; asm volatile("ld.global.cg.b32 %0, [%1];" : "=r"(v) : "l"(p) : "memory"); return v; }
__device__ __forceinline__ void bulk_g2s(uint32_t dst, const void* src, int bytes, uint32_t bar) {
    asm volatile("fence.proxy.async.global;\ncp.async.bulk.shared::cluster.global.mbarrier::complete_tx::bytes [%0], [%1], %2, [%3];"
                 ::"r"(dst), "l"(src), "r"(bytes), "r"(bar) : "memory");
}
__device__ __forceinline__ void bulk_s2g(void* dst, uint32_t src, int bytes) {
    asm volatile("cp.async.bulk.global.shared::cta.bulk_group [%0], [%1], %2;" ::"l"(dst), "r"(src), "r"(bytes) : "memory");
}
__device__ __forceinline__ void bulk_commit() { asm volatile("cp.async.bulk.commit_group;" ::: "memory"); }
__device__ __forceinline__ void bulk_wait_all() { asm volatile("cp.async.bulk.wait_group 0;" ::: "memory"); }
__device__ __forceinline__ void fence_async_smem() { asm volatile("fence.proxy.async.shared::cta;" ::: "memory"); }
__device__ __forceinline__ void stsm4(uint32_t a, uint32_t r0, uint32_t r1, uint32_t r2, uint32_t r3) {
    asm volatile("stmatrix.sync.aligned.m8n8.x4.shared.b16 [%0], {%1,%2,%3,%4};" ::"r"(a), "r"(r0), "r"(r1), "r"(r2), "r"(r3) : "memory");
}
__device__ __forceinline__ void prefetch_tmap(const CUtensorMap* tm) { asm volatile("prefetch.tensormap [%0];" ::"l"(tm) : "memory"); }
__device__ __forceinline__ void wg_fence() { asm volatile("wgmma.fence.sync.aligned;" ::: "memory"); }
__device__ __forceinline__ void wg_commit() { asm volatile("wgmma.commit_group.sync.aligned;" ::: "memory"); }
template <int N> __device__ __forceinline__ void wg_wait() { asm volatile("wgmma.wait_group.sync.aligned %0;" ::"n"(N) : "memory"); }
__device__ __forceinline__ uint64_t mkdesc(uint32_t addr, uint32_t lbo, uint32_t sbo, uint32_t swz) {
    return (uint64_t)((addr & 0x3FFFF) >> 4) | ((uint64_t)(lbo >> 4) << 16) | ((uint64_t)(sbo >> 4) << 32) | ((uint64_t)swz << 62);
}
template <int N> __device__ __forceinline__ void pin(float (&r)[N]) {
#pragma unroll
    for (int i = 0; i < N; i++) asm volatile("" : "+f"(r[i])::"memory");
}
template <int N> __device__ __forceinline__ void pin(uint32_t (&r)[N]) {
#pragma unroll
    for (int i = 0; i < N; i++) asm volatile("" : "+r"(r[i])::"memory");
}
__device__ __forceinline__ float ex2(float x) { float y; asm("ex2.approx.ftz.f32 %0, %1;" : "=f"(y) : "f"(x)); return y; }
__device__ __forceinline__ uint32_t pack2(float lo, float hi) { uint32_t r; asm("cvt.rn.bf16x2.f32 %0, %1, %2;" : "=r"(r) : "f"(hi), "f"(lo)); return r; }
__device__ __forceinline__ uint32_t hfma2(uint32_t a, uint32_t b, uint32_t c) { uint32_t d; asm("fma.rn.bf16x2 %0, %1, %2, %3;" : "=r"(d) : "r"(a), "r"(b), "r"(c)); return d; }
__device__ __forceinline__ float bf_lo(uint32_t v) { return __uint_as_float(v << 16); }
__device__ __forceinline__ float bf_hi(uint32_t v) { return __uint_as_float(v & 0xffff0000u); }
__device__ __forceinline__ void mma16816(float (&c)[4], uint32_t a0, uint32_t a1, uint32_t a2, uint32_t a3, uint32_t b0, uint32_t b1) {
    asm volatile("mma.sync.aligned.m16n8k16.row.col.f32.bf16.bf16.f32 {%0,%1,%2,%3}, {%4,%5,%6,%7}, {%8,%9}, {%0,%1,%2,%3};"
                 : "+f"(c[0]), "+f"(c[1]), "+f"(c[2]), "+f"(c[3]) : "r"(a0), "r"(a1), "r"(a2), "r"(a3), "r"(b0), "r"(b1));
}
__device__ __forceinline__ void mma1688(float (&c)[4], uint32_t a0, uint32_t a1, uint32_t b0) {
    asm volatile("mma.sync.aligned.m16n8k8.row.col.f32.bf16.bf16.f32 {%0,%1,%2,%3}, {%4,%5}, {%6}, {%0,%1,%2,%3};"
                 : "+f"(c[0]), "+f"(c[1]), "+f"(c[2]), "+f"(c[3]) : "r"(a0), "r"(a1), "r"(b0));
}
__device__ __forceinline__ uint32_t movm_t(uint32_t a) { uint32_t d; asm volatile("movmatrix.sync.aligned.m8n8.trans.b16 %0, %1;" : "=r"(d) : "r"(a)); return d; }
__device__ __forceinline__ void stg128(void* p, uint4 v) { asm volatile("st.global.v4.b32 [%0], {%1,%2,%3,%4};" ::"l"(p), "r"(v.x), "r"(v.y), "r"(v.z), "r"(v.w) : "memory"); }
__device__ __forceinline__ void stg64(void* p, uint32_t a, uint32_t b) { asm volatile("st.global.v2.b32 [%0], {%1,%2};" ::"l"(p), "r"(a), "r"(b) : "memory"); }
__device__ __forceinline__ int frag_pos(int warp4, int lane) { return ((lane & 2) << 5) | (warp4 << 4) | ((lane >> 2) << 1) | (lane & 1); }
__device__ __forceinline__ bool elect_one() {
    uint32_t p;
    asm volatile("{\n.reg .pred p;\nelect.sync _|p, 0xffffffff;\nselp.u32 %0, 1, 0, p;\n}\n" : "=r"(p));
    return p;
}
__device__ __forceinline__ uint32_t clock_lo() { uint32_t v; asm volatile("mov.u32 %0, %%clock;" : "=r"(v)); return v; }
__device__ __forceinline__ int fresh_bid() { int v; asm volatile("mov.u32 %0, %%ctaid.x;" : "=r"(v)); return v; }
__device__ __forceinline__ int fresh_wid() { int v; asm volatile("mov.u32 %0, %%tid.x;" : "=r"(v)); return __shfl_sync(0xffffffffu, v >> 5, 0); }
__device__ __forceinline__ int here(int v) { asm volatile("" : "+r"(v)); return v; }
__device__ __forceinline__ int fresh_tid() { int v; asm volatile("mov.u32 %0, %%tid.x;" : "=r"(v)); return v; }
__device__ __forceinline__ uint32_t lds32(uint32_t a) { uint32_t v; asm volatile("ld.shared.b32 %0, [%1];" : "=r"(v) : "r"(a) : "memory"); return v; }
__device__ __forceinline__ uint4 lds128(uint32_t a) { uint4 v; asm volatile("ld.shared.v4.b32 {%0,%1,%2,%3}, [%4];" : "=r"(v.x), "=r"(v.y), "=r"(v.z), "=r"(v.w) : "r"(a)); return v; }

__device__ __forceinline__ void wgmma_ss128(float (&d)[64], uint64_t da, uint64_t db, int sd) {
    asm volatile("{\n.reg .pred p;\nsetp.ne.b32 p, %66, 0;\n"
        "wgmma.mma_async.sync.aligned.m64n128k16.f32.bf16.bf16 "
        "{%0,%1,%2,%3,%4,%5,%6,%7,%8,%9,%10,%11,%12,%13,%14,%15,%16,%17,%18,%19,"
        "%20,%21,%22,%23,%24,%25,%26,%27,%28,%29,%30,%31,%32,%33,%34,%35,%36,%37,%38,%39,"
        "%40,%41,%42,%43,%44,%45,%46,%47,%48,%49,%50,%51,%52,%53,%54,%55,%56,%57,%58,%59,"
        "%60,%61,%62,%63}, "
        "%64, %65, p, 1, 1, 0, 1;\n}\n"
        : "+f"(d[0]), "+f"(d[1]), "+f"(d[2]), "+f"(d[3]), "+f"(d[4]), "+f"(d[5]), "+f"(d[6]), "+f"(d[7]), "+f"(d[8]), "+f"(d[9]),
          "+f"(d[10]), "+f"(d[11]), "+f"(d[12]), "+f"(d[13]), "+f"(d[14]), "+f"(d[15]), "+f"(d[16]), "+f"(d[17]), "+f"(d[18]), "+f"(d[19]),
          "+f"(d[20]), "+f"(d[21]), "+f"(d[22]), "+f"(d[23]), "+f"(d[24]), "+f"(d[25]), "+f"(d[26]), "+f"(d[27]), "+f"(d[28]), "+f"(d[29]),
          "+f"(d[30]), "+f"(d[31]), "+f"(d[32]), "+f"(d[33]), "+f"(d[34]), "+f"(d[35]), "+f"(d[36]), "+f"(d[37]), "+f"(d[38]), "+f"(d[39]),
          "+f"(d[40]), "+f"(d[41]), "+f"(d[42]), "+f"(d[43]), "+f"(d[44]), "+f"(d[45]), "+f"(d[46]), "+f"(d[47]), "+f"(d[48]), "+f"(d[49]),
          "+f"(d[50]), "+f"(d[51]), "+f"(d[52]), "+f"(d[53]), "+f"(d[54]), "+f"(d[55]), "+f"(d[56]), "+f"(d[57]), "+f"(d[58]), "+f"(d[59]),
          "+f"(d[60]), "+f"(d[61]), "+f"(d[62]), "+f"(d[63])
        : "l"(da), "l"(db), "r"(sd));
}
__device__ __forceinline__ void wgmma_ss112(float (&d)[56], uint64_t da, uint64_t db, int sd) {
    asm volatile("{\n.reg .pred p;\nsetp.ne.b32 p, %58, 0;\n"
        "wgmma.mma_async.sync.aligned.m64n112k16.f32.bf16.bf16 "
        "{%0,%1,%2,%3,%4,%5,%6,%7,%8,%9,%10,%11,%12,%13,%14,%15,%16,%17,%18,%19,"
        "%20,%21,%22,%23,%24,%25,%26,%27,%28,%29,%30,%31,%32,%33,%34,%35,%36,%37,%38,%39,"
        "%40,%41,%42,%43,%44,%45,%46,%47,%48,%49,%50,%51,%52,%53,%54,%55}, "
        "%56, %57, p, 1, 1, 0, 1;\n}\n"
        : "+f"(d[0]), "+f"(d[1]), "+f"(d[2]), "+f"(d[3]), "+f"(d[4]), "+f"(d[5]), "+f"(d[6]), "+f"(d[7]), "+f"(d[8]), "+f"(d[9]),
          "+f"(d[10]), "+f"(d[11]), "+f"(d[12]), "+f"(d[13]), "+f"(d[14]), "+f"(d[15]), "+f"(d[16]), "+f"(d[17]), "+f"(d[18]), "+f"(d[19]),
          "+f"(d[20]), "+f"(d[21]), "+f"(d[22]), "+f"(d[23]), "+f"(d[24]), "+f"(d[25]), "+f"(d[26]), "+f"(d[27]), "+f"(d[28]), "+f"(d[29]),
          "+f"(d[30]), "+f"(d[31]), "+f"(d[32]), "+f"(d[33]), "+f"(d[34]), "+f"(d[35]), "+f"(d[36]), "+f"(d[37]), "+f"(d[38]), "+f"(d[39]),
          "+f"(d[40]), "+f"(d[41]), "+f"(d[42]), "+f"(d[43]), "+f"(d[44]), "+f"(d[45]), "+f"(d[46]), "+f"(d[47]), "+f"(d[48]), "+f"(d[49]),
          "+f"(d[50]), "+f"(d[51]), "+f"(d[52]), "+f"(d[53]), "+f"(d[54]), "+f"(d[55])
        : "l"(da), "l"(db), "r"(sd));
}
__device__ __forceinline__ void wgmma_rs80(float (&d)[40], uint32_t a0, uint32_t a1, uint32_t a2, uint32_t a3, uint64_t db) {
    asm volatile("{\n.reg .pred p;\nsetp.eq.b32 p, 0, 0;\n"
        "wgmma.mma_async.sync.aligned.m64n80k16.f32.bf16.bf16 "
        "{%0,%1,%2,%3,%4,%5,%6,%7,%8,%9,%10,%11,%12,%13,%14,%15,%16,%17,%18,%19,"
        "%20,%21,%22,%23,%24,%25,%26,%27,%28,%29,%30,%31,%32,%33,%34,%35,%36,%37,%38,%39}, "
        "{%40,%41,%42,%43}, %44, p, 1, 1, 1;\n}\n"
        : "+f"(d[0]), "+f"(d[1]), "+f"(d[2]), "+f"(d[3]), "+f"(d[4]), "+f"(d[5]), "+f"(d[6]), "+f"(d[7]), "+f"(d[8]), "+f"(d[9]),
          "+f"(d[10]), "+f"(d[11]), "+f"(d[12]), "+f"(d[13]), "+f"(d[14]), "+f"(d[15]), "+f"(d[16]), "+f"(d[17]), "+f"(d[18]), "+f"(d[19]),
          "+f"(d[20]), "+f"(d[21]), "+f"(d[22]), "+f"(d[23]), "+f"(d[24]), "+f"(d[25]), "+f"(d[26]), "+f"(d[27]), "+f"(d[28]), "+f"(d[29]),
          "+f"(d[30]), "+f"(d[31]), "+f"(d[32]), "+f"(d[33]), "+f"(d[34]), "+f"(d[35]), "+f"(d[36]), "+f"(d[37]), "+f"(d[38]), "+f"(d[39])
        : "r"(a0), "r"(a1), "r"(a2), "r"(a3), "l"(db));
}
__device__ __forceinline__ void wgmma_rs80f(float (&d)[40], uint32_t a0, uint32_t a1, uint32_t a2, uint32_t a3, uint64_t db) {
    asm volatile("{\n.reg .pred p;\nsetp.ne.b32 p, 0, 0;\n"
        "wgmma.mma_async.sync.aligned.m64n80k16.f32.bf16.bf16 "
        "{%0,%1,%2,%3,%4,%5,%6,%7,%8,%9,%10,%11,%12,%13,%14,%15,%16,%17,%18,%19,"
        "%20,%21,%22,%23,%24,%25,%26,%27,%28,%29,%30,%31,%32,%33,%34,%35,%36,%37,%38,%39}, "
        "{%40,%41,%42,%43}, %44, p, 1, 1, 1;\n}\n"
        : "=f"(d[0]), "=f"(d[1]), "=f"(d[2]), "=f"(d[3]), "=f"(d[4]), "=f"(d[5]), "=f"(d[6]), "=f"(d[7]), "=f"(d[8]), "=f"(d[9]),
          "=f"(d[10]), "=f"(d[11]), "=f"(d[12]), "=f"(d[13]), "=f"(d[14]), "=f"(d[15]), "=f"(d[16]), "=f"(d[17]), "=f"(d[18]), "=f"(d[19]),
          "=f"(d[20]), "=f"(d[21]), "=f"(d[22]), "=f"(d[23]), "=f"(d[24]), "=f"(d[25]), "=f"(d[26]), "=f"(d[27]), "=f"(d[28]), "=f"(d[29]),
          "=f"(d[30]), "=f"(d[31]), "=f"(d[32]), "=f"(d[33]), "=f"(d[34]), "=f"(d[35]), "=f"(d[36]), "=f"(d[37]), "=f"(d[38]), "=f"(d[39])
        : "r"(a0), "r"(a1), "r"(a2), "r"(a3), "l"(db));
}
__device__ __forceinline__ void wgmma_qk0(float (&d)[32], uint32_t a0, uint32_t a1, uint32_t a2, uint32_t a3, uint64_t db) {
    asm volatile("{\n.reg .pred p;\nsetp.ne.b32 p, 0, 0;\n"
        "wgmma.mma_async.sync.aligned.m64n64k16.f32.bf16.bf16 "
        "{%0,%1,%2,%3,%4,%5,%6,%7,%8,%9,%10,%11,%12,%13,%14,%15,%16,%17,%18,%19,"
        "%20,%21,%22,%23,%24,%25,%26,%27,%28,%29,%30,%31}, "
        "{%32,%33,%34,%35}, %36, p, 1, 1, 0;\n}\n"
        : "=f"(d[0]), "=f"(d[1]), "=f"(d[2]), "=f"(d[3]), "=f"(d[4]), "=f"(d[5]), "=f"(d[6]), "=f"(d[7]), "=f"(d[8]), "=f"(d[9]),
          "=f"(d[10]), "=f"(d[11]), "=f"(d[12]), "=f"(d[13]), "=f"(d[14]), "=f"(d[15]), "=f"(d[16]), "=f"(d[17]), "=f"(d[18]), "=f"(d[19]),
          "=f"(d[20]), "=f"(d[21]), "=f"(d[22]), "=f"(d[23]), "=f"(d[24]), "=f"(d[25]), "=f"(d[26]), "=f"(d[27]), "=f"(d[28]), "=f"(d[29]),
          "=f"(d[30]), "=f"(d[31])
        : "r"(a0), "r"(a1), "r"(a2), "r"(a3), "l"(db));
}
__device__ __forceinline__ void wgmma_qk1(float (&d)[32], uint32_t a0, uint32_t a1, uint32_t a2, uint32_t a3, uint64_t db) {
    asm volatile("{\n.reg .pred p;\nsetp.eq.b32 p, 0, 0;\n"
        "wgmma.mma_async.sync.aligned.m64n64k16.f32.bf16.bf16 "
        "{%0,%1,%2,%3,%4,%5,%6,%7,%8,%9,%10,%11,%12,%13,%14,%15,%16,%17,%18,%19,"
        "%20,%21,%22,%23,%24,%25,%26,%27,%28,%29,%30,%31}, "
        "{%32,%33,%34,%35}, %36, p, 1, 1, 0;\n}\n"
        : "+f"(d[0]), "+f"(d[1]), "+f"(d[2]), "+f"(d[3]), "+f"(d[4]), "+f"(d[5]), "+f"(d[6]), "+f"(d[7]), "+f"(d[8]), "+f"(d[9]),
          "+f"(d[10]), "+f"(d[11]), "+f"(d[12]), "+f"(d[13]), "+f"(d[14]), "+f"(d[15]), "+f"(d[16]), "+f"(d[17]), "+f"(d[18]), "+f"(d[19]),
          "+f"(d[20]), "+f"(d[21]), "+f"(d[22]), "+f"(d[23]), "+f"(d[24]), "+f"(d[25]), "+f"(d[26]), "+f"(d[27]), "+f"(d[28]), "+f"(d[29]),
          "+f"(d[30]), "+f"(d[31])
        : "r"(a0), "r"(a1), "r"(a2), "r"(a3), "l"(db));
}
__device__ __forceinline__ void wgmma_pv(float (&d)[12], uint32_t a0, uint32_t a1, uint32_t a2, uint32_t a3, uint64_t db) {
    asm volatile("{\n.reg .pred p;\nsetp.eq.b32 p, 0, 0;\n"
        "wgmma.mma_async.sync.aligned.m64n24k16.f32.bf16.bf16 "
        "{%0,%1,%2,%3,%4,%5,%6,%7,%8,%9,%10,%11}, "
        "{%12,%13,%14,%15}, %16, p, 1, 1, 1;\n}\n"
        : "+f"(d[0]), "+f"(d[1]), "+f"(d[2]), "+f"(d[3]), "+f"(d[4]), "+f"(d[5]), "+f"(d[6]), "+f"(d[7]), "+f"(d[8]), "+f"(d[9]),
          "+f"(d[10]), "+f"(d[11])
        : "r"(a0), "r"(a1), "r"(a2), "r"(a3), "l"(db));
}
__device__ __forceinline__ void wgmma_pvn(float (&d)[12], uint32_t a0, uint32_t a1, uint32_t a2, uint32_t a3, uint64_t db) {
    asm volatile("{\n.reg .pred p;\nsetp.eq.b32 p, 0, 0;\n"
        "wgmma.mma_async.sync.aligned.m64n24k16.f32.bf16.bf16 "
        "{%0,%1,%2,%3,%4,%5,%6,%7,%8,%9,%10,%11}, "
        "{%12,%13,%14,%15}, %16, p, -1, 1, 1;\n}\n"
        : "+f"(d[0]), "+f"(d[1]), "+f"(d[2]), "+f"(d[3]), "+f"(d[4]), "+f"(d[5]), "+f"(d[6]), "+f"(d[7]), "+f"(d[8]), "+f"(d[9]),
          "+f"(d[10]), "+f"(d[11])
        : "r"(a0), "r"(a1), "r"(a2), "r"(a3), "l"(db));
}
__device__ __forceinline__ void wgmma_pv0(float (&d)[12], uint32_t a0, uint32_t a1, uint32_t a2, uint32_t a3, uint64_t db) {
    asm volatile("{\n.reg .pred p;\nsetp.ne.b32 p, 0, 0;\n"
        "wgmma.mma_async.sync.aligned.m64n24k16.f32.bf16.bf16 "
        "{%0,%1,%2,%3,%4,%5,%6,%7,%8,%9,%10,%11}, "
        "{%12,%13,%14,%15}, %16, p, 1, 1, 1;\n}\n"
        : "=f"(d[0]), "=f"(d[1]), "=f"(d[2]), "=f"(d[3]), "=f"(d[4]), "=f"(d[5]), "=f"(d[6]), "=f"(d[7]), "=f"(d[8]), "=f"(d[9]),
          "=f"(d[10]), "=f"(d[11])
        : "r"(a0), "r"(a1), "r"(a2), "r"(a3), "l"(db));
}
__device__ __forceinline__ void wgmma_l64a(float (&d)[32], uint64_t da, uint64_t db) {
    asm volatile("{\n.reg .pred p;\nsetp.ne.b32 p, 0, 0;\n"
        "wgmma.mma_async.sync.aligned.m64n64k16.f32.bf16.bf16 "
        "{%0,%1,%2,%3,%4,%5,%6,%7,%8,%9,%10,%11,%12,%13,%14,%15,%16,%17,%18,%19,"
        "%20,%21,%22,%23,%24,%25,%26,%27,%28,%29,%30,%31}, "
        "%32, %33, p, 1, 1, 0, 0;\n}\n"
        : "=f"(d[0]), "=f"(d[1]), "=f"(d[2]), "=f"(d[3]), "=f"(d[4]), "=f"(d[5]), "=f"(d[6]), "=f"(d[7]), "=f"(d[8]), "=f"(d[9]),
          "=f"(d[10]), "=f"(d[11]), "=f"(d[12]), "=f"(d[13]), "=f"(d[14]), "=f"(d[15]), "=f"(d[16]), "=f"(d[17]), "=f"(d[18]), "=f"(d[19]),
          "=f"(d[20]), "=f"(d[21]), "=f"(d[22]), "=f"(d[23]), "=f"(d[24]), "=f"(d[25]), "=f"(d[26]), "=f"(d[27]), "=f"(d[28]), "=f"(d[29]),
          "=f"(d[30]), "=f"(d[31])
        : "l"(da), "l"(db));
}
__device__ __forceinline__ void wgmma_l64b(float (&d)[32], uint64_t da, uint64_t db) {
    asm volatile("{\n.reg .pred p;\nsetp.eq.b32 p, 0, 0;\n"
        "wgmma.mma_async.sync.aligned.m64n64k16.f32.bf16.bf16 "
        "{%0,%1,%2,%3,%4,%5,%6,%7,%8,%9,%10,%11,%12,%13,%14,%15,%16,%17,%18,%19,"
        "%20,%21,%22,%23,%24,%25,%26,%27,%28,%29,%30,%31}, "
        "%32, %33, p, 1, 1, 0, 0;\n}\n"
        : "+f"(d[0]), "+f"(d[1]), "+f"(d[2]), "+f"(d[3]), "+f"(d[4]), "+f"(d[5]), "+f"(d[6]), "+f"(d[7]), "+f"(d[8]), "+f"(d[9]),
          "+f"(d[10]), "+f"(d[11]), "+f"(d[12]), "+f"(d[13]), "+f"(d[14]), "+f"(d[15]), "+f"(d[16]), "+f"(d[17]), "+f"(d[18]), "+f"(d[19]),
          "+f"(d[20]), "+f"(d[21]), "+f"(d[22]), "+f"(d[23]), "+f"(d[24]), "+f"(d[25]), "+f"(d[26]), "+f"(d[27]), "+f"(d[28]), "+f"(d[29]),
          "+f"(d[30]), "+f"(d[31])
        : "l"(da), "l"(db));
}
__device__ __forceinline__ void wgmma_l16a(float (&d)[8], uint64_t da, uint64_t db) {
    asm volatile("{\n.reg .pred p;\nsetp.ne.b32 p, 0, 0;\n"
        "wgmma.mma_async.sync.aligned.m64n16k16.f32.bf16.bf16 "
        "{%0,%1,%2,%3,%4,%5,%6,%7}, "
        "%8, %9, p, 1, 1, 0, 0;\n}\n"
        : "=f"(d[0]), "=f"(d[1]), "=f"(d[2]), "=f"(d[3]), "=f"(d[4]), "=f"(d[5]), "=f"(d[6]), "=f"(d[7])
        : "l"(da), "l"(db));
}
__device__ __forceinline__ void wgmma_l16b(float (&d)[8], uint64_t da, uint64_t db) {
    asm volatile("{\n.reg .pred p;\nsetp.eq.b32 p, 0, 0;\n"
        "wgmma.mma_async.sync.aligned.m64n16k16.f32.bf16.bf16 "
        "{%0,%1,%2,%3,%4,%5,%6,%7}, "
        "%8, %9, p, 1, 1, 0, 0;\n}\n"
        : "+f"(d[0]), "+f"(d[1]), "+f"(d[2]), "+f"(d[3]), "+f"(d[4]), "+f"(d[5]), "+f"(d[6]), "+f"(d[7])
        : "l"(da), "l"(db));
}

__device__ __forceinline__ uint32_t exp2_pair_fma(float a, float b) {
    const uint32_t y = __byte_perm(__float_as_uint(a), __float_as_uint(b), 0x6521);
    const uint32_t z = 0xFE7BFE7Bu - y;
    const uint32_t e = hfma2(y, z, 0x3F053F05u);
    return hfma2(y, e, y);
}
__device__ __forceinline__ void exp_tile(const float (&s)[32], uint32_t (&p)[16], const int MASK) {
#pragma unroll
    for (int j = 0; j < 8; j++) {
        if ((MASK >> (j >> 1)) & 1) { p[2 * j] = exp2_pair_fma(s[4 * j], s[4 * j + 1]); p[2 * j + 1] = exp2_pair_fma(s[4 * j + 2], s[4 * j + 3]); }
        else { p[2 * j] = pack2(ex2(s[4 * j]), ex2(s[4 * j + 1])); p[2 * j + 1] = pack2(ex2(s[4 * j + 2]), ex2(s[4 * j + 3])); }
    }
}
__device__ __forceinline__ void qk_tile(float (&s)[32], const uint32_t (&q)[8], uint64_t dk0, uint64_t dk1) {
    wgmma_qk0(s, q[0], q[1], q[2], q[3], dk0);
    wgmma_qk1(s, q[4], q[5], q[6], q[7], dk1);
}
__device__ __forceinline__ void pv_tile(float (&o)[12], const uint32_t (&p)[16], uint64_t dv, int mask) {
#pragma unroll
    for (int k = 0; k < 4; k++) {
        if ((mask >> k) & 1) wgmma_pvn(o, p[4 * k], p[4 * k + 1], p[4 * k + 2], p[4 * k + 3], dv + k * 48);
        else wgmma_pv(o, p[4 * k], p[4 * k + 1], p[4 * k + 2], p[4 * k + 3], dv + k * 48);
    }
}
__device__ __forceinline__ void finish_o(const float (&o)[12], uint32_t (&w)[6], int odd, float g0, float g1, int lane, float& l0, float& l1) {
    const int src = (lane & ~3) | (odd ? 0 : 2);
    l0 = __shfl_sync(0xffffffffu, o[8], src);
    l1 = __shfl_sync(0xffffffffu, o[10], src);
    float r0, r1;
    asm("rcp.approx.ftz.f32 %0, %1;" : "=f"(r0) : "f"(l0));
    asm("rcp.approx.ftz.f32 %0, %1;" : "=f"(r1) : "f"(l1));
    const float f0 = g0 * r0, f1 = g1 * r1;
#pragma unroll
    for (int d = 0; d < 3; d++) { w[2 * d] = pack2(o[4 * d] * f0, o[4 * d + 1] * f0); w[2 * d + 1] = pack2(o[4 * d + 2] * f1, o[4 * d + 3] * f1); }
}
__device__ __forceinline__ void store_o(const uint32_t (&w)[6], int row16, int h, int gbase, int lane) {
    uint2* p = g_att + ((row16 >> 2) * 160 + gbase + 5 * (h >> 1)) * 128 + frag_pos(row16 & 3, lane);
    const int off = (h & 1) ? 3 * 128 : 0;
    stg64(p + off, w[0], w[1]);
    stg64(p + off + 128, w[2], w[3]);
    if (((lane & 3) >= 2) == ((h & 1) != 0)) stg64(p + 2 * 128, w[4], w[5]);
}

#define PACE 300u
#define PROMO CU_TENSOR_MAP_L2_PROMOTION_L2_256B
#define MAP 1
#define P1_NT(b) ((b) >> 4)
#define P1_MP(b) (((b) >> 1) & 7)
#define LJ 16
#define DEFER 4
#define FENCE2()
#define P1_NTA(nt) (((nt) + 3) & 7)
#define S3J 22
#define S3T 14
#define S1T 9
#define S4J 20
#define S4T 5
#define S1J 10
constexpr int SLOT = 24576;
constexpr int OFF_X = 98304, OFF_R = 6 * SLOT, OFF_L = OFF_R - 1536, OFF_BAR = 9 * SLOT;
constexpr int SMEM_BYTES = OFF_BAR + 1024 + 64;
enum { B_FULL = 0, B_EMPTY = 48, B_STGB = 96, B_STGA = 104, B_RET = 112, B_NRM = 144, B_HLP = 152, B_KV = 160, B_HDR = 192, B_L = 200, B_WO = 208, B_XCH = 248, B_AF = 264, B_LD = 328, B_R26 = 336, B_AE = 344, B_W0 = 376, B_ZERO = 400, B_MISC = 416, B_PUB = 1024 };
__host__ __device__ constexpr int k_off(int j) {
    return j < 8 ? (7 + (j >> 2)) * SLOT + (j & 3) * 3072 : j == 8 ? OFF_R - 6144 : j < 20 ? 3 * SLOT + (j - 9) * 3072 : j < 26 ? 36864 + (j - 20) * 3072 : (j - 26) * 3072;
}
__host__ __device__ constexpr int v_off(int j) { return k_off(j) + (j < 8 ? 4 : j == 8 ? 1 : j < 20 ? 11 : 6) * 3072; }
__host__ __device__ constexpr int wo_off(int i) { return 3 * SLOT + (i < 7 ? i : i - 7) * 20480; }
__host__ __device__ constexpr int wo_bar(int i) { return i < 3 ? 0 : i < 7 ? 1 : i - 5; }
constexpr float SCORE_LIMIT2 = 118.f * 118.f;

__device__ __forceinline__ void load_kv(uint32_t sb, int h, int i, int j0, int n, int arm) {
    const uint32_t bar = sb + OFF_BAR + B_KV + 8 * i;
    if (arm) mbar_expect_tx(bar, arm * 6144);
    bulk_g2s(sb + k_off(j0), g_qkv + (size_t)(32 + h) * HEAD_BYTES + j0 * 3072, n * 3072, bar);
    bulk_g2s(sb + v_off(j0), g_qkv + (size_t)(64 + h) * HEAD_BYTES + j0 * 3072, n * 3072, bar);
}
__device__ __forceinline__ void load_wo(uint32_t sb, int seq, int n) {
    const uint32_t bar = sb + OFF_BAR + B_WO + 8 * wo_bar(seq);
    mbar_expect_tx(bar, n * 20480);
    bulk_g2s(sb + wo_off(seq), reinterpret_cast<const uint8_t*>(g_wo) + (blockIdx.x & 7) * 204800 + seq * 20480, n * 20480, bar);
}

__device__ __forceinline__ void local_attn(uint32_t sb, int wid) {
    const uint32_t sL = sb + OFF_L;
    const int tid = fresh_tid(), lane = tid & 31, g = lane >> 2, t2 = (lane & 3) * 2;
    const int wg = wid >> 2, w = wid & 3;
    const int bid = fresh_bid(), h = bid >> 2, qb = bid & 3;
    const float* gp = g_gate + qb * 512 + wg * 128 + w * 16 + g;
    const float gt[4] = {ldcg_f32(gp), ldcg_f32(gp + 8), ldcg_f32(gp + 64), ldcg_f32(gp + 72)};
    const bool cur0 = t2 <= g, cur1 = t2 < g;
    mbar_wait(sb + OFF_BAR + B_L, 0);
    float v0[4], v1[4];
    {
        const uint32_t tq = sL + wg * 6144;
        const uint64_t dq0 = mkdesc(tq, 128, 384, 0), dq1 = mkdesc(tq + 256, 0, 384, 0);
        float sa[2][32], sc[2][8];
        wg_fence();
#pragma unroll
        for (int b = 0; b < 2; b++) {
            wgmma_l64a(sa[b], dq0 + b * 192, dq0 + b * 192 + (24576 >> 4)); wgmma_l64b(sa[b], dq1 + b * 192, dq1 + b * 192 + (24576 >> 4));
            wgmma_l16a(sc[b], dq0 + b * 192, dq0 + b * 192 + (27648 >> 4)); wgmma_l16b(sc[b], dq1 + b * 192, dq1 + b * 192 + (27648 >> 4));
        }
        wg_commit(); wg_wait<0>(); pin(sa[0]); pin(sa[1]); pin(sc[0]); pin(sc[1]);
#define LS(B, BLK, R, E) ((BLK) < 4 ? sa[B][((BLK) * 8 + (R) * 6 + (E)) & 31] : sc[B][(R) * 6 + (E)])
#define LWIN(W) { _Pragma("unroll") for (int i = 0; i < 4; i++) { v0[i] = cur0 ? LS(i >> 1, (W) + 1, i & 1, 0) : LS(i >> 1, W, i & 1, 0); \
                                                                 v1[i] = cur1 ? LS(i >> 1, (W) + 1, i & 1, 1) : LS(i >> 1, W, i & 1, 1); } }
        if (w == 0) LWIN(0) else if (w == 1) LWIN(1) else if (w == 2) LWIN(2) else LWIN(3)
#undef LWIN
#undef LS
    }
    if (qb == 0 && wid == 0) {
        if (!cur0) v0[0] = v0[1] = -INFINITY;
        if (!cur1) v1[0] = v1[1] = -INFINITY;
    }
    float m[4], l[4];
#pragma unroll
    for (int i = 0; i < 4; i++) m[i] = fmaxf(v0[i], v1[i]);
#pragma unroll
    for (int i = 0; i < 4; i++) m[i] = fmaxf(m[i], __shfl_xor_sync(0xffffffffu, m[i], 1));
#pragma unroll
    for (int i = 0; i < 4; i++) m[i] = fmaxf(m[i], __shfl_xor_sync(0xffffffffu, m[i], 2));
#pragma unroll
    for (int i = 0; i < 4; i++) { v0[i] = ex2(v0[i] - m[i]); v1[i] = ex2(v1[i] - m[i]); l[i] = v0[i] + v1[i]; }
#pragma unroll
    for (int i = 0; i < 4; i++) l[i] += __shfl_xor_sync(0xffffffffu, l[i], 1);
#pragma unroll
    for (int i = 0; i < 4; i++) l[i] += __shfl_xor_sync(0xffffffffu, l[i], 2);
    uint32_t pp[4];
#pragma unroll
    for (int i = 0; i < 4; i++) {
        float r;
        asm("rcp.approx.ftz.f32 %0, %1;" : "=f"(r) : "f"(l[i]));
        r *= gt[i];
        pp[i] = pack2(v0[i] * r, v1[i] * r);
    }
    const uint32_t mc = (cur0 ? 0xffffu : 0u) | (cur1 ? 0xffff0000u : 0u);
    uint32_t p[2][20];
#pragma unroll
    for (int ks = 0; ks < 5; ks++) {
        const uint32_t mk = ks == w ? ~mc : ks == w + 1 ? mc : 0u;
#pragma unroll
        for (int b = 0; b < 2; b++) { p[b][4 * ks] = pp[2 * b] & mk; p[b][4 * ks + 1] = p[b][4 * ks + 2] = 0u; p[b][4 * ks + 3] = pp[2 * b + 1] & mk; }
    }
    pin(p[0]); pin(p[1]);
    const uint64_t dv = mkdesc(sL + 24576 + 25344 + wg * 6144, 384, 128, 0);
    float o[2][12];
    wg_fence();
#pragma unroll
    for (int b = 0; b < 2; b++) {
        wgmma_pv0(o[b], p[b][0], p[b][1], p[b][2], p[b][3], dv + b * 192);
#pragma unroll
        for (int ks = 1; ks < 5; ks++) wgmma_pv(o[b], p[b][4 * ks], p[b][4 * ks + 1], p[b][4 * ks + 2], p[b][4 * ks + 3], dv + b * 192 + ks * 48);
    }
    wg_commit();
    wg_wait<0>(); pin(o[0]); pin(o[1]);
#pragma unroll
    for (int b = 0; b < 2; b++) {
        uint32_t wv[6];
#pragma unroll
        for (int i = 0; i < 6; i++) wv[i] = pack2(o[b][2 * i], o[b][2 * i + 1]);
        store_o(wv, qb * 32 + wg * 8 + b * 4 + w, h, 0, lane);
    }
    __syncwarp();
    if (elect_one()) mbar_arrive(sb + OFF_BAR + B_LD);
    TR2(7, tid == 64);
}

__device__ __noinline__ void exact_rows(int h, int row16, int lane) {
    const bool aug_lane = ((lane & 3) >= 2) != ((h & 1) != 0);
    const uint8_t* a = g_qkv + (size_t)h * HEAD_BYTES + row16 * 768 + lane * 4;
    const uint8_t* gk = g_qkv + (size_t)(32 + h) * HEAD_BYTES + lane * 4;
    const uint8_t* gv = g_qkv + (size_t)(64 + h) * HEAD_BYTES + lane * 4;
    const uint32_t q0 = ldcg_u32(a), q1 = ldcg_u32(a + 384), q2 = ldcg_u32(a + 128), q3 = ldcg_u32(a + 512);
    const uint32_t q4 = aug_lane ? 0u : ldcg_u32(a + 256), q5 = aug_lane ? 0u : ldcg_u32(a + 640);
    float m0 = -INFINITY, m1 = -INFINITY;
#pragma unroll 4
    for (int kg = 0; kg < 256; kg++) {
        const uint8_t* ka = gk + kg * 384;
        float c[4] = {0.f, 0.f, 0.f, 0.f};
        mma16816(c, q0, q1, q2, q3, ldcg_u32(ka), ldcg_u32(ka + 128));
        mma1688(c, q4, q5, ldcg_u32(ka + 256));
        m0 = fmaxf(m0, fmaxf(c[0], c[1])); m1 = fmaxf(m1, fmaxf(c[2], c[3]));
    }
    m0 = fmaxf(m0, __shfl_xor_sync(0xffffffffu, m0, 1)); m1 = fmaxf(m1, __shfl_xor_sync(0xffffffffu, m1, 1));
    m0 = fmaxf(m0, __shfl_xor_sync(0xffffffffu, m0, 2)); m1 = fmaxf(m1, __shfl_xor_sync(0xffffffffu, m1, 2));
    float oc[3][4];
#pragma unroll
    for (int d = 0; d < 3; d++) oc[d][0] = oc[d][1] = oc[d][2] = oc[d][3] = 0.f;
#pragma unroll 2
    for (int kg = 0; kg < 256; kg += 2) {
        uint32_t kk[2][3], vv[2][3], pp[2][2];
#pragma unroll
        for (int e = 0; e < 2; e++)
#pragma unroll
            for (int d = 0; d < 3; d++) { kk[e][d] = ldcg_u32(gk + (kg + e) * 384 + d * 128); vv[e][d] = ldcg_u32(gv + (kg + e) * 384 + d * 128); }
#pragma unroll
        for (int e = 0; e < 2; e++) {
            float c[4] = {0.f, 0.f, 0.f, 0.f};
            mma16816(c, q0, q1, q2, q3, kk[e][0], kk[e][1]);
            mma1688(c, q4, q5, kk[e][2]);
            pp[e][0] = pack2(ex2(c[0] - m0), ex2(c[1] - m0));
            pp[e][1] = pack2(ex2(c[2] - m1), ex2(c[3] - m1));
        }
#pragma unroll
        for (int d = 0; d < 3; d++) mma16816(oc[d], pp[0][0], pp[0][1], pp[1][0], pp[1][1], movm_t(vv[0][d]), movm_t(vv[1][d]));
    }
    float o[12];
#pragma unroll
    for (int i = 0; i < 12; i++) o[i] = oc[i >> 2][i & 3];
    const int row = row16 * 16 + (lane >> 2);
    float l0, l1;
    uint32_t w[6];
    finish_o(o, w, h & 1, 1.f - ldcg_f32(g_gate + row), 1.f - ldcg_f32(g_gate + row + 8), lane, l0, l1);
    store_o(w, row16, h, 80, lane);
}

__device__ __forceinline__ uint32_t frag_off(int mh, int part) { return part == 0 ? 36864 + mh * 16384 : mh * 36864 + (part - 1) * 16384; }
__device__ __forceinline__ void load_frag(uint32_t sb, int bid, int mh, int part) {
    const uint32_t fb = sb + OFF_BAR + B_AF + mh * 32 + part * 8;
    mbar_expect_tx(fb, 16384);
    bulk_g2s(sb + frag_off(mh, part),
             g_att + (((bid >> 5) * 8 + mh * 4 + ((bid >> 3) & 3)) * 160 + (bid & 1) * 40 + (part ? 64 + part * 16 : 0)) * 128, 16384, fb);
}
__device__ __forceinline__ uint32_t* atta_out(int bid) { return g_flag + (F_ATTA + (bid & 3) * 2 + (bid >> 6)) * 32; }
__device__ __forceinline__ uint32_t* attb_out(int bid, int wg) { return g_flag + (F_ATTB + ((bid & 3) * 4 + wg) * 2 + (bid >> 6)) * 32; }
__device__ __forceinline__ uint32_t* atta_in(int bid) { return g_flag + (F_ATTA + (bid >> 5) * 2 + (bid & 1)) * 32; }
__device__ __forceinline__ uint32_t* attb_in(int bid) { return g_flag + (F_ATTB + (bid >> 3) * 2 + (bid & 1)) * 32; }
#define SVC __forceinline__
__device__ SVC void service(uint32_t sb, int step, uint32_t aflag) {
    const uint32_t bars = sb + OFF_BAR;
    const int bid = fresh_bid(), h = bid >> 2, qb = bid & 3;
    if (step == 0) {
        bulk_wait_all();
        flag_add_done(g_flag + (F_QKVA + P1_NTA(P1_NT(bid))) * 32);
        load_kv(sb, h, 3, 20, 6, 12); load_kv(sb, h, 3, 26, 6, 0);
    } else if (step == 3) {
        mbar_wait(bars + B_RET + 24, 0);
        load_wo(sb, 0, 3); load_wo(sb, 3, 4);
    } else if (step == 4) {
        mbar_wait(bars + B_LD, 0);
        flag_add_done(atta_out(bid));
    } else if (step == 2) {
        if (aflag >= 16) {
            mbar_wait(bars + B_R26, 0);
            asm volatile("fence.acquire.gpu;" ::: "memory");
            load_frag(sb, bid, 0, 0); load_frag(sb, bid, 1, 0);
        }
    } else {
        mbar_wait(bars + B_RET, 0);
        fence_async_smem();
        const int halo = qb ? 768 : 0;
        const uint8_t* src = g_qkv + (size_t)(96 + h) * HEAD_BYTES + qb * 24576;
        mbar_expect_tx(bars + B_L, 3 * 24576 + 2 * halo);
        bulk_g2s(sb + OFF_L, src, 24576, bars + B_L);
        bulk_g2s(sb + OFF_L + 24576 + 768 - halo, src + (size_t)32 * HEAD_BYTES - halo, 24576 + halo, bars + B_L);
        bulk_g2s(sb + OFF_L + 24576 + 25344 + 768 - halo, src + (size_t)64 * HEAD_BYTES - halo, 24576 + halo, bars + B_L);
    }
}

__global__ void __cluster_dims__(2, 1, 1) __launch_bounds__(512, 1)
k_fused(const __grid_constant__ CUtensorMap tmX, const __grid_constant__ CUtensorMap tmWb, const __grid_constant__ CUtensorMap tmWa,
        const __grid_constant__ CUtensorMap tmS, const __nv_bfloat16* __restrict__ x, const __nv_bfloat16* __restrict__ gate_w,
        const uint8_t* __restrict__ woa, const uint8_t* __restrict__ wob,
        __nv_bfloat16* __restrict__ out) {
    extern __shared__ __align__(1024) uint8_t smem_raw[];
    const uint32_t sb = smem_u32(smem_raw);
    if (sb & 1023u) __trap();
    const uint32_t bars = sb + OFF_BAR;
    float* s_misc = reinterpret_cast<float*>(smem_raw + OFF_BAR + B_MISC);
    const int bid = blockIdx.x;
    const int h = bid >> 2, qb = bid & 3;

    {
        const int warp = __shfl_sync(0xffffffffu, threadIdx.x >> 5, 0), lane = threadIdx.x & 31;
        const int mt = P1_MP(bid) * 2 + (bid & 1), nt = P1_NT(bid);
        TRINIT(); TR(0, threadIdx.x == 0);
        if (threadIdx.x == 352) {
            prefetch_tmap(&tmX);
#pragma unroll
            for (int i = 0; i < 6; i++) mbar_init(bars + B_FULL + 8 * i, 1);
            fence_mbar_init();
        } else if (threadIdx.x == 256) {
            prefetch_tmap(&tmWb);
        } else if (threadIdx.x == 32) {
#pragma unroll
            for (int i = 0; i < 6; i++) mbar_init(bars + B_EMPTY + 8 * i, 16);
#pragma unroll
            for (int i = 0; i < 4; i++) mbar_init(bars + B_PUB + 8 * i, 4);
            fence_mbar_init();
        } else if (threadIdx.x == 64) {
            mbar_init(bars + B_STGB, 8); mbar_init(bars + B_STGA, 8);
            mbar_init(bars + B_RET, 16); mbar_init(bars + B_RET + 8, 8); mbar_init(bars + B_RET + 16, 16); mbar_init(bars + B_RET + 24, 16);
            mbar_init(bars + B_LD, 16); mbar_init(bars + B_NRM, 4); mbar_init(bars + B_HLP, 4);
            fence_mbar_init();
        } else if (threadIdx.x == 128) {
#pragma unroll
            for (int i = 0; i < 10; i++) mbar_init(bars + B_XCH + 8 * i, 1);
            fence_mbar_init();
        } else if (threadIdx.x == 160) {
            mbar_init(bars + B_AE, 8); mbar_init(bars + B_R26, 16); mbar_init(bars + B_W0, 8); mbar_init(bars + B_W0 + 8, 8); mbar_init(bars + B_W0 + 16, 8);
            fence_mbar_init();
        } else if (threadIdx.x == 96) {
#pragma unroll
            for (int i = 0; i < 11; i++) mbar_init(bars + B_KV + 8 * i, i == 3 ? 2 : 1);
            s_misc[-4] = 0.f; s_misc[-3] = 0.f;
            fence_mbar_init();
        }
        __syncwarp();
        cluster_arrive();
        if (warp == 11 && elect_one()) {
#pragma unroll
            for (int i = 0; i < 3; i++) {
                mbar_expect_tx(bars + B_FULL + 16 * i, 32768);
                tma_x(sb + OFF_X + i * 16384, &tmX, i * 64, mt * 8, bars + B_FULL + 16 * i);
                mbar_expect_tx(bars + B_FULL + 16 * i + 8, 16384);
            }
        }
        __syncwarp();
        cluster_wait();
        if ((warp == 8 || warp == 10) && elect_one()) {
            const int col = (bid & 1) * 128 + (warp == 10 ? 64 : 0);
#pragma unroll
            for (int i = 0; i < 6; i++) tma_3d_mc(sb + i * 16384 + col * 64, &tmWb, col, nt, i * 32, bars + B_FULL + 8 * i, 3);
        }
        __syncwarp();

        if (warp < 8) {
            asm volatile("setmaxnreg.inc.sync.aligned.u32 152;");
            const int wg = warp >> 2, t = lane & 3;
            float acc0[64], acc1[56];
#pragma unroll
            for (int i = 0; i < 64; i++) acc0[i] = 0.f;
#pragma unroll
            for (int i = 0; i < 56; i++) acc1[i] = 0.f;
            pin(acc0); pin(acc1);
            const uint64_t da0 = mkdesc(sb + OFF_X + wg * 8192, 16, 1024, 1), db0 = mkdesc(sb, 4096, 1024, 1);
            uint32_t rel;
            asm volatile("mapa.shared::cluster.u32 %0, %1, %2;" : "=r"(rel) : "r"(bars + B_EMPTY), "r"(lane & 1));
            uint32_t xs = 0, xprev = 0, ph = 0;
#pragma unroll 1
            for (int br = 0; br < 2; br++) {
#pragma unroll 1
                for (int kp = 0; kp < 10; kp++) {
                    const uint64_t da = da0 + xs * 1024, db = db0 + xs * 2048;
#pragma unroll
                    for (int e = 0; e < 2; e++) {
                        mbar_wait(bars + B_FULL + 16 * xs + 8 * e, ph);
                        TR(1 + 3 * br, threadIdx.x == 0 && kp + e == 0);
                        wg_fence();
                        wgmma_ss128(acc0, da + e * 4, db + e * 1024, e ? 1 : kp);
                        wgmma_ss112(acc1, da + e * 4, db + e * 1024 + 512, e ? 1 : kp);
                        wgmma_ss128(acc0, da + e * 4 + 2, db + e * 1024 + 128, 1);
                        wgmma_ss112(acc1, da + e * 4 + 2, db + e * 1024 + 640, 1);
                        wg_commit();
                        wg_wait<1>();
                        if (lane < 2 && kp + e > 0) asm volatile("mbarrier.arrive.shared::cluster.b64 _, [%0];" ::"r"(e ? rel + 16 * xs : rel + 16 * xprev + 8) : "memory");
                    }
                    xprev = xs;
                    if (++xs == 3) { xs = 0; ph ^= 1; }
                }
                wg_wait<0>();
                pin(acc0); pin(acc1);
                if (lane < 2) asm volatile("mbarrier.arrive.shared::cluster.b64 _, [%0];" ::"r"(rel + 16 * xprev + 8) : "memory");
                TR(2 + 3 * br, threadIdx.x == 0);
                if (br == 1) named_sync(1, 256);
                else mbar_wait(bars + B_HDR, 0);
                const uint32_t wst = sb + (br == 0 ? OFF_R : 0) + warp * 768 + (lane & 7) * 16;
                const uint32_t a0 = wst + (lane >> 3) * 128;
                const uint32_t a1 = wst + (lane < 16 ? 512 + (lane >> 3) * 128 : 6144 + ((lane >> 3) - 2) * 128);
                const uint32_t a2 = wst + 6144 + 256 + (lane >> 3) * 128;
                const bool poly = (POLY16 >> ((mt * 8 + warp) & 15)) & 1;
                const uint32_t augq = br ? 0u : (t & 1) ? 0x00003D2Du : 0x3F8043C0u;
                const uint32_t augk = br ? 0u : (t & 1) ? (poly ? 0u : 0x00003F80u) : (poly ? 0x00003F80u : 0x3F800000u);
                const uint32_t augv = (t & 1) ? 0u : 0x00003F80u;
                const float sc2 = br ? 0.5f * QSCALE : QSCALE;
                const int hp0 = (br ? P1_NTA(nt) : nt) * 6;
#pragma unroll
                for (int u = 0; u < 6; u++) {
                    uint32_t v[2][5];
#define ACC(i) ((i) < 64 ? acc0[(i) & 63] : acc1[((i) - 64) % 56])
                    if (hp0 + u < 16) {
#pragma unroll
                        for (int j = 0; j < 10; j++) {
                            const int i = (5 * u + j % 5) * 4 + 2 * (j / 5);
                            const float f = j % 5 == 2 ? sc2 : QSCALE;
                            v[j / 5][j % 5] = pack2(ACC(i) * f, ACC(i + 1) * f);
                        }
                    } else {
#pragma unroll
                        for (int j = 0; j < 10; j++) { const int i = (5 * u + j % 5) * 4 + 2 * (j / 5); v[j / 5][j % 5] = pack2(ACC(i), ACC(i + 1)); }
                    }
#undef ACC
                    const uint32_t aug = hp0 + u < 16 ? augq : hp0 + u < 32 ? augk : augv;
                    stsm4(a0 + u * 12288, v[0][0], v[0][1], t < 2 ? v[0][2] : aug, v[1][0]);
                    stsm4(a1 + u * 12288, v[1][1], t < 2 ? v[1][2] : aug, v[0][3], v[0][4]);
                    stsm4(a2 + u * 12288, t < 2 ? aug : v[0][2], v[1][3], v[1][4], t < 2 ? aug : v[1][2]);
                }
                fence_async_smem();
                __syncwarp();
                if (lane == 0) mbar_arrive(bars + B_STGB + 8 * br);
                TR(3 + 3 * br, threadIdx.x == 0);
            }
            asm volatile("setmaxnreg.dec.sync.aligned.u32 128;");
        } else if (warp < 12) {
            asm volatile("setmaxnreg.dec.sync.aligned.u32 80;");
            if (warp != 9) {
                if (warp == 11) {
                    uint32_t xs = 0, ph = 0;
#pragma unroll 1
                    for (int P = 3; P < 20; P++) {
                        const int k0 = (P < 10 ? P : P - 13) * 64;
                        mbar_wait(bars + B_EMPTY + 16 * xs + 8, ph);
                        if (elect_one()) {
                            if (k0 >= 0) tma_x(sb + OFF_X + xs * 16384, &tmX, k0, mt * 8, bars + B_FULL + 16 * xs);
                            if (P == 7) { prefetch_tmap(&tmWa); prefetch_tmap(&tmS); }
                        }
                        if (++xs == 3) { xs = 0; ph ^= 1; }
                    }
                } else {
                    const int col = (bid & 1) * 128 + (warp == 10 ? 64 : 0);
                    uint32_t s = 0, ph = 0;
#pragma unroll 1
                    for (int it = 6; it < 40; it++) {
                        const int k0 = (it < 20 ? it : it < 26 ? it - 6 : it - 26) * 32;
                        const CUtensorMap* tw = it >= 20 ? &tmWa : &tmWb;
                        const int ct = it >= 20 ? P1_NTA(nt) : nt;
                        const int bytes = ((s & 1) || (it >= 20 && it < 26)) ? 16384 : 32768;
                        mbar_wait(bars + B_EMPTY + 8 * s, ph);
                        if (elect_one()) {
                            tma_3d_mc(sb + s * 16384 + col * 64, tw, col, ct, k0, bars + B_FULL + 8 * s, 3);
                            if (warp == 8) mbar_expect_tx(bars + B_FULL + 8 * s, bytes);
                        }
                        if (++s == 6) { s = 0; ph ^= 1; }
                    }
                }
                if (warp == 8 && elect_one()) {
                    mbar_wait(bars + B_KV, 0);
                    load_kv(sb, h, 1, 4, 4, 6);
                    bulk_g2s(sb + OFF_R + 12288, g_qkv + (size_t)h * HEAD_BYTES + qb * 24576 + 12288, 12288, bars + B_KV + 8);
                    mbar_wait(bars + B_EMPTY + 24, 0);
                    load_kv(sb, h, 2, 8, 1, 12); load_kv(sb, h, 2, 9, 11, 0);
                }
            } else {
                if (elect_one()) {
                    mbar_wait(bars + B_HLP, 0);
                    bulk_s2g(g_wo + bid * 800, sb + OFF_R, 12800);
                    bulk_s2g(g_gate + bid * 16, sb + OFF_R + 12800, 64);
                    bulk_commit();
                    bulk_wait_all();
                    mbar_arrive(bars + B_HDR);
                    flag_add_done(g_flag + F_HELP * 32);
                    TR2(53, true);
                    mbar_wait(bars + B_STGB, 0);
                    uint32_t tick = clock_lo();
#pragma unroll 1
                    for (int i = 0; i < 24; i++) {
                        while (clock_lo() - tick < PACE) {}
                        tick += PACE;
                        bulk_s2g(g_qkv + (size_t)(nt * 12 + (i >> 1)) * HEAD_BYTES + mt * 6144 + (i & 1) * 3072, sb + OFF_R + i * 3072, 3072);
                    }
                    mbar_wait(bars + B_NRM, 0);
                    bulk_s2g(g_nrm + mt * 96 + nt * 12, bars + B_MISC, 48);
                    bulk_commit();
                    bulk_wait_all();
                    flag_add_done(g_flag + (F_QKVB + nt) * 32);
                    TR(8, true);
                    flag_wait_head(g_flag + F_QKVB * 32, h, 128);
                    fence_async_smem();
                    TR(9, true);
                    load_kv(sb, h, 0, 0, 4, 6);
                    bulk_g2s(sb + OFF_R, g_qkv + (size_t)h * HEAD_BYTES + qb * 24576, 12288, bars + B_KV);
                }
                __syncwarp();
                {
                    const uint32_t w = ldcg_u32(g_nrm + (lane < 16 ? lane * 96 + 32 + h : (qb * 4 + (lane & 3)) * 96 + h));
                    const float kn = __uint_as_float(__reduce_max_sync(0xffffffffu, lane < 16 ? w : 0u));
                    if (lane >= 16 && lane < 20) s_misc[lane] = __uint_as_float(w) * kn <= SCORE_LIMIT2 ? 0.f : 1.f;
                    __syncwarp();
                    if (elect_one()) mbar_arrive(bars + B_KV + 24);
                }
            }
            __syncwarp();
            named_sync(5, 128);
            asm volatile("setmaxnreg.inc.sync.aligned.u32 128;");
        } else {
            mbar_wait(bars + B_FULL, 0);
            {
                uint4 wv[7];
#pragma unroll
                for (int e = 0; e < 7; e++) {
                    const int i = threadIdx.x - 384 + e * 128, d = bid * 800 + i;
                    const int kr = d & 7, ng = (d >> 3) % 20, kg = (d / 160) % 80, part = bid >> 4;
                    const int k = (kg < 40 ? kg : kg + 40) * 8 + (part & 1) * 320 + kr;
                    const uint8_t* src = (k < 640 ? woa + k * 1280 : wob + (k - 640) * 1280) + ((part >> 1) * 20 + ng) * 16;
                    if (i < 800) wv[e] = __ldg(reinterpret_cast<const uint4*>(src));
                }
                const uint2* gw = reinterpret_cast<const uint2*>(gate_w) + lane;
                const uint2* xr = reinterpret_cast<const uint2*>(x + (size_t)(bid * 16 + (warp - 12) * 4) * DM) + lane;
                uint2 gv[5], xv[4][5];
#pragma unroll
                for (int i = 0; i < 5; i++) gv[i] = __ldg(gw + 32 * i);
#pragma unroll
                for (int i = 0; i < 20; i++) xv[i / 5][i % 5] = __ldg(xr + 32 * i);
                float a[4];
#pragma unroll
                for (int e = 0; e < 4; e++) {
                    a[e] = 0.f;
#pragma unroll
                    for (int i = 0; i < 5; i++) {
                        a[e] = fmaf(bf_lo(xv[e][i].x), bf_lo(gv[i].x), a[e]); a[e] = fmaf(bf_hi(xv[e][i].x), bf_hi(gv[i].x), a[e]);
                        a[e] = fmaf(bf_lo(xv[e][i].y), bf_lo(gv[i].y), a[e]); a[e] = fmaf(bf_hi(xv[e][i].y), bf_hi(gv[i].y), a[e]);
                    }
                }
#pragma unroll
                for (int o = 16; o; o >>= 1) {
#pragma unroll
                    for (int e = 0; e < 4; e++) a[e] += __shfl_xor_sync(0xffffffffu, a[e], o);
                }
                const float z = lane == 0 ? a[0] : lane == 1 ? a[1] : lane == 2 ? a[2] : a[3];
                if (lane < 4) asm volatile("st.shared.f32 [%0], %1;" ::"r"(sb + OFF_R + 12800 + ((lane & 1) * 8 + (warp - 12) * 2 + (lane >> 1)) * 4), "f"(__fdividef(1.f, 1.f + __expf(-z))) : "memory");
#pragma unroll
                for (int e = 0; e < 7; e++) {
                    const int i = threadIdx.x - 384 + e * 128;
                    if (i < 800) asm volatile("st.shared.v4.b32 [%0], {%1,%2,%3,%4};" ::"r"(sb + OFF_R + i * 16), "r"(wv[e].x), "r"(wv[e].y), "r"(wv[e].z), "r"(wv[e].w) : "memory");
                }
                fence_async_smem();
                __syncwarp();
                if (lane == 0) mbar_arrive(bars + B_HLP);
            }
            mbar_wait(bars + B_STGB, 0);
#pragma unroll 1
            for (int hs = warp - 12; hs < 12; hs += 4) {
                uint32_t nm = 0;
                if (nt * 12 + hs < 64) {
#pragma unroll
                    for (int i = 0; i < 4; i++) {
                        const uint32_t a = sb + OFF_R + hs * 6144 + (i * 4 + (lane >> 3)) * 384 + (lane & 7) * 16;
                        const uint4 k0 = lds128(a), k1 = lds128(a + 128);
                        uint32_t k2, k3;
                        asm volatile("ld.shared.v2.b32 {%0,%1}, [%2];" : "=r"(k2), "=r"(k3) : "r"(a + 256 + (hs & 1) * 8));
                        uint32_t n0 = hfma2(k2, k2, 0u), n1 = hfma2(k3, k3, 0u);
                        n0 = hfma2(k0.x, k0.x, n0); n1 = hfma2(k0.y, k0.y, n1); n0 = hfma2(k0.z, k0.z, n0); n1 = hfma2(k0.w, k0.w, n1);
                        n0 = hfma2(k1.x, k1.x, n0); n1 = hfma2(k1.y, k1.y, n1); n0 = hfma2(k1.z, k1.z, n0); n1 = hfma2(k1.w, k1.w, n1);
                        nm = max(nm, __float_as_uint((bf_lo(n0) + bf_hi(n0)) + (bf_lo(n1) + bf_hi(n1))));
                    }
                }
                nm = __reduce_max_sync(0xffffffffu, nm);
                if (lane == 0) s_misc[hs] = __uint_as_float(nm) * 1.03f;
            }
            fence_async_smem();
            __syncwarp();
            if (lane == 0) mbar_arrive(bars + B_NRM);
        }
    }

    uint32_t aflag;
    {
        const uint64_t dK0 = mkdesc(sb, 128, 384, 0), dK1 = mkdesc(sb + 256, 0, 384, 0), dV = mkdesc(sb, 384, 128, 0);
        const int wid = fresh_wid();
        mbar_wait(bars + B_KV, 0);
        TR(10 + (threadIdx.x >> 7), (threadIdx.x & 127) == 0);
#pragma unroll 1
        for (int u = 0; u < 2; u++) {
            uint32_t q[8];
            {
                const uint32_t a = sb + OFF_R + (u * 32 + here(wid) * 2) * 384 + (fresh_tid() & 31) * 4;
                q[0] = lds32(a); q[1] = lds32(a + 384); q[2] = lds32(a + 128); q[3] = lds32(a + 512);
                q[4] = lds32(a + 256); q[5] = lds32(a + 640);
                q[6] = lds32(bars + B_ZERO); q[7] = lds32(bars + B_ZERO + 4);
            }
            float o[12];
#pragma unroll
            for (int i = 0; i < 12; i++) o[i] = 0.f;
            pin(o); pin(q);
            float s0[32], s1[32];
            uint32_t p[16];
            float g0, g1;
            TR2(48 + u, fresh_tid() == 128);
            wg_fence(); qk_tile(s0, q, dK0 + (k_off(0) >> 4), dK1 + (k_off(0) >> 4)); wg_commit();
#pragma unroll
            for (int j = 0; j < 32; j += 2) {
                FENCE2(); qk_tile(s1, q, dK0 + (k_off(j + 1) >> 4), dK1 + (k_off(j + 1) >> 4)); wg_commit();
                wg_wait<1>(); pin(s0);
                exp_tile(s0, p, POLY16 >> (4 * (j & 3)));
                pin(p);
                wg_fence(); pv_tile(o, p, dV + (v_off(j) >> 4), POLY16 >> (4 * (j & 3))); wg_commit();
                if (j == 2 || j == 6 || j == 18) { mbar_wait(bars + B_KV + (j == 2 ? 8 : j == 6 ? 16 : 24), 0); wg_fence(); }
                const bool ahead = j + 2 < 32 && j != LJ;
                if (ahead) { FENCE2(); qk_tile(s0, q, dK0 + (k_off(j + 2) >> 4), dK1 + (k_off(j + 2) >> 4)); wg_commit(); }
                {
                    TR(32 + u * 4 + j / 8, (j & 7) == 0 && fresh_tid() == 128);
                    if (j == 10) { if (u == 1 && elect_one()) mbar_arrive(bars + B_RET); }
                    if (j == 4) {
                        if (u == 0 && wid == 14 && elect_one()) {
                            const int bid = fresh_bid();
                            mbar_wait(bars + B_STGA, 0);
                            tma_store_3d(&tmS, sb, 0, (P1_MP(bid) * 2 + (bid & 1)) * 16, 96 + P1_NTA(P1_NT(bid)) * 12);
                            bulk_commit();
                        }
                        __syncwarp();
                    }
                    if (j == 12) {
                        if (u == 0 && wid == 14 && elect_one()) service(sb, 0, 0);
                        __syncwarp();
                    }
                    if (j == S1J) { if (u == 1 && wid == S1T && elect_one()) service(sb, 1, 0); __syncwarp(); }
                    if (j == 20 || j == 26) { if (u == 1 && elect_one()) mbar_arrive(bars + (j == 20 ? B_RET + 24 : B_R26)); }
                    if (j == S4J) { if (u == 1 && wid == S4T && elect_one()) service(sb, 4, 0); __syncwarp(); }
                    if (j == S3J) { if (u == 1 && wid == S3T && elect_one()) service(sb, 3, 0); __syncwarp(); }
                    if (j == 28) { if (u == 1 && wid == 10 && elect_one()) service(sb, 2, aflag); __syncwarp(); }
                    if (j == 26) {
                        const float* gp = g_gate + (fresh_bid() & 3) * 512 + u * 256 + here(wid) * 16 + ((fresh_tid() & 31) >> 2);
                        g0 = ldcg_f32(gp); g1 = ldcg_f32(gp + 8);
                        aflag = ld_relaxed(atta_in(fresh_bid()));
                    }
                }
                if (ahead) wg_wait<1>(); else wg_wait<0>();
                pin(s1);
                exp_tile(s1, p, POLY16 >> (4 * ((j + 1) & 3)));
                pin(p);
                wg_fence(); pv_tile(o, p, dV + (v_off(j + 1) >> 4), POLY16 >> (4 * ((j + 1) & 3))); wg_commit();
                if (j == LJ) {
                    TR2(27, j == LJ && u == 1 && fresh_tid() == 64);
                    wg_wait<0>();
                    if (u == 1) local_attn(sb, here(wid));
                    wg_fence(); qk_tile(s0, q, dK0 + (k_off(j + 2) >> 4), dK1 + (k_off(j + 2) >> 4)); wg_commit();
                }
            }
            const int tid = fresh_tid(), lane = tid & 31, warp = here(wid);
            const int bid = fresh_bid(), h = bid >> 2, qb = bid & 3;
            TR2(50 + u, tid == 128);
            if (u == 0 && wid == 13 && elect_one())
                flag_wait_head(g_flag + F_QKVA * 32, h, 0);
            __syncwarp();
            wg_wait<0>(); pin(o);
            TR(14 + u * 4 + (tid >> 7), (tid & 127) == 0);
            if (u == 1 && lane == 0) mbar_arrive(bars + B_RET + 16);
            float l0, l1;
            uint32_t w[6];
            finish_o(o, w, h & 1, 1.f - g0, 1.f - g1, lane, l0, l1);
            store_o(w, qb * 32 + u * 16 + warp, h, 80, lane);
            const float sum = (((o[0] + o[1]) + (o[2] + o[3])) + ((o[4] + o[5]) + (o[6] + o[7]))) + ((o[8] + o[9]) + (o[10] + o[11]));
            if (__any_sync(0xffffffffu, !(l0 >= 9.3132257e-10f && l1 >= 9.3132257e-10f && fabsf(sum) <= 1e37f && s_misc[16 + u * 2 + (warp >> 3)] == 0.f)))
                exact_rows(h, qb * 32 + u * 16 + warp, lane);
        }
        __syncwarp();
        if (elect_one()) mbar_arrive(bars + B_PUB + (wid >> 2) * 8);
    }

    {
        const int tid = fresh_tid(), lane = tid & 31;
        const int warp = __shfl_sync(0xffffffffu, tid >> 5, 0);
        const int bid = fresh_bid(), rank = bid & 1;
        if (warp >= 8) {
            asm volatile("setmaxnreg.dec.sync.aligned.u32 40;");
            if ((warp == 8 || warp == 9 || warp == 12 || warp == 14) && elect_one()) {
                const int wg = warp == 9 ? 0 : warp == 14 ? 1 : warp >> 2;
                mbar_wait(bars + B_PUB + 8 * wg, 0);
                flag_add_done(attb_out(bid, wg));
            }
            if (warp == 13 && elect_one()) {
                mbar_expect_tx(bars + B_XCH, 20480); mbar_expect_tx(bars + B_XCH + 8, 20480);
#pragma unroll
                for (int i = 0; i < 3; i++) { mbar_wait(bars + B_W0 + 8 * i, 0); load_wo(sb, 7 + i, 1); }
                TR2(57, true);
            }
            if (warp == 10 && elect_one()) {
                if (aflag < 16) flag_wait(atta_in(bid), 16);
                mbar_wait(bars + B_RET + 16, 0);
                if (aflag < 16) { load_frag(sb, bid, 0, 0); load_frag(sb, bid, 1, 0); }
                load_frag(sb, bid, 0, 1); load_frag(sb, bid, 0, 2);
                TR2(56, true);
            }
            if (warp == 11 && elect_one()) {
                flag_wait(attb_in(bid), 16);
                TR2(52, true);
                mbar_wait(bars + B_AE, 0);
                fence_async_smem();
                load_frag(sb, bid, 1, 1); load_frag(sb, bid, 1, 2);
                if (atomicAdd(g_flag + F_EXIT * 32, 1u) == 127u) {
#pragma unroll 1
                    for (int i = 0; i < F_COUNT; i++) g_flag[i * 32] = 0u;
                }
            }
        } else {
            const int mh = warp >> 2;
            const int mt64 = (bid >> 5) * 8 + mh * 4 + ((bid >> 3) & 3);
            const int pos = frag_pos(warp & 3, lane);
            const uint2* ap = g_att + (mt64 * 160 + rank * 40) * 128 + pos;
            const uint32_t as0 = sb + frag_off(mh, 0) + pos * 8, as1 = sb + frag_off(mh, 1) + pos * 8, fb = bars + B_AF + mh * 32;
            const uint64_t db = mkdesc(sb, 2560, 128, 0);
            TR(22, tid == 0); TR2(55, tid == 0 && aflag >= 16);
            uint32_t a[6][16];
            auto ldg = [&](int i) {
#pragma unroll
                for (int j = 0; j < 8; j++)
                    asm volatile("ld.global.L1::no_allocate.v2.b32 {%0, %1}, [%2];" : "=r"(a[i % 6][2 * j]), "=r"(a[i % 6][2 * j + 1])
                                 : "l"(ap + ((i / 5) * 80 + (i % 5) * 8 + j) * 128) : "memory");
            };
            auto lds = [&](int i) {
                if (i == 0 || i == 5 || i == 7) mbar_wait(fb + (i / 3) * 8, 0);
#pragma unroll
                for (int j = 0; j < 8; j++)
                    asm volatile("ld.shared.v2.b32 {%0, %1}, [%2];" : "=r"(a[i % 6][2 * j]), "=r"(a[i % 6][2 * j + 1])
                                 : "r"((i < 5 ? as0 : as1) + ((i % 5) * 8 + j) * 1024) : "memory");
            };
            asm volatile("setmaxnreg.inc.sync.aligned.u32 216;");
            float snd[40], keep[40];
            const uint64_t dk = db + rank * 80, ds = db + (rank ^ 1) * 80;
            TR(23, tid == 0);
            auto half = [&](float (&acc)[40], uint64_t d, int i) {
#pragma unroll
                for (int k = 0; k < 4; k++)
                    if (i + k == 0) wgmma_rs80f(acc, a[0][0], a[0][1], a[0][2], a[0][3], d + (wo_off(0) >> 4));
                    else wgmma_rs80(acc, a[i % 6][4 * k], a[i % 6][4 * k + 1], a[i % 6][4 * k + 2], a[i % 6][4 * k + 3], d + (wo_off(i) >> 4) + k * 320);
            };
            auto mma = [&](int i) {
                if (i == 0 || wo_bar(i) != wo_bar(i - 1)) mbar_wait(bars + B_WO + 8 * wo_bar(i), 0);
                pin(a[i % 6]);
                TR2(24, tid == 0 && i == 0); TR2(61, tid == 192 && i == 1); TR2(62, tid == 192 && i == 4); TR2(63, tid == 192 && i == 5);
                wg_fence();
                half(snd, ds, i);
                if (i < 10 - DEFER) half(keep, dk, i);
                wg_commit();
            };
            lds(0); lds(1);
            mma(0);
            ldg(2); ldg(3);
            mma(1);
            if (lane == 0) mbar_arrive(bars + B_AE);
            ldg(4);
#pragma unroll
            for (int i = 0; i < 3; i++) {
                wg_wait<1>();
                if (lane == 0) mbar_arrive(bars + B_W0 + 8 * i);
                mma(i + 2);
            }
            wg_wait<0>();
            if (lane == 0) mbar_arrive_cluster(bars + B_RET + 8, rank ^ 1);
            lds(5); mma(5);
            ldg(9); lds(6); mma(6);
            lds(7); lds(8);
            mma(7); mma(8); mma(9);
#pragma unroll
            for (int i = 10 - DEFER; i < 10; i++) half(keep, dk, i);
            wg_commit();
            const uint32_t xs = sb + (mh ? wo_off(4) : wo_off(3)) + (tid & 127) * 16;
            {
                uint32_t ra, rb;
                asm volatile("mapa.shared::cluster.u32 %0, %1, %2;" : "=r"(ra) : "r"(xs), "r"(rank ^ 1));
                asm volatile("mapa.shared::cluster.u32 %0, %1, %2;" : "=r"(rb) : "r"(bars + B_XCH + 8 * mh), "r"(rank ^ 1));
                mbar_wait(bars + B_RET + 8, 0);
                wg_wait<1>();
                pin(snd);
#pragma unroll
                for (int j = 0; j < 10; j++)
                    asm volatile("st.async.weak.shared::cluster.mbarrier::complete_tx::bytes.v4.f32 [%0], {%1,%2,%3,%4}, [%5];"
                                 ::"r"(ra + j * 2048), "f"(snd[4 * j]), "f"(snd[4 * j + 1]), "f"(snd[4 * j + 2]), "f"(snd[4 * j + 3]), "r"(rb) : "memory");
            }
            named_sync(8 + mh, 128);
            mbar_wait(bars + B_XCH + 8 * mh, 0);
            TR2(58, tid == 192);
            uint4 rcv[10];
#pragma unroll
            for (int j = 0; j < 10; j++) rcv[j] = lds128(xs + j * 2048);
            wg_wait<0>();
            pin(keep);
            TR2(25, tid == 0); TR2(60, tid == 192);
            uint32_t w[20];
#pragma unroll
            for (int j = 0; j < 10; j++) {
                const uint4 o = rcv[j];
                w[2 * j] = pack2(keep[4 * j] + __uint_as_float(o.x), keep[4 * j + 1] + __uint_as_float(o.y));
                w[2 * j + 1] = pack2(keep[4 * j + 2] + __uint_as_float(o.z), keep[4 * j + 3] + __uint_as_float(o.w));
            }
            const uint32_t ot = sb + frag_off(mh, 1) + (warp & 3) * 2816;
            const uint32_t sa = ot + (lane & 15) * 176 + (lane >> 4) * 16;
#pragma unroll
            for (int j = 0; j < 5; j++) stsm4(sa + j * 32, w[4 * j], w[4 * j + 1], w[4 * j + 2], w[4 * j + 3]);
            __syncwarp();
            __nv_bfloat16* ob = out + (size_t)(mt64 * 64 + (warp & 3) * 16) * DM + (bid & 7) * 80;
#pragma unroll
            for (int i = 0; i < 5; i++) {
                const int c = lane + 32 * i, r = c / 10;
                stg128(ob + ((r & 7) * 2 + (r >> 3)) * DM + (c % 10) * 8, lds128(ot + r * 176 + (c % 10) * 16));
            }
            TR2(26, tid == 0); TR2(59, tid == 192);
            TRFLUSH();
        }
    }
}

typedef CUresult (*EncodeFn)(CUtensorMap*, CUtensorMapDataType, cuuint32_t, void*, const cuuint64_t*, const cuuint64_t*,
                             const cuuint32_t*, const cuuint32_t*, CUtensorMapInterleave, CUtensorMapSwizzle,
                             CUtensorMapL2promotion, CUtensorMapFloatOOBfill);

void make_map(EncodeFn fn, CUtensorMap* tm, const void* ptr, int rank, const cuuint64_t* dims, const cuuint64_t* strides,
              const cuuint32_t* box, CUtensorMapSwizzle swz) {
    const cuuint32_t es[4] = {1, 1, 1, 1};
    fn(tm, CU_TENSOR_MAP_DATA_TYPE_BFLOAT16, rank, const_cast<void*>(ptr), dims, strides, box, es, CU_TENSOR_MAP_INTERLEAVE_NONE,
       swz, PROMO, CU_TENSOR_MAP_FLOAT_OOB_FILL_NONE);
}

}

extern "C" void kernel_launch(void* const* d_in, const int* in_sizes, int n_in, void* d_out, int out_size) {
    (void)in_sizes; (void)n_in; (void)out_size;
    const __nv_bfloat16* x = (const __nv_bfloat16*)d_in[0];
    const __nv_bfloat16* wqkv_a = (const __nv_bfloat16*)d_in[1];
    const __nv_bfloat16* wo_a = (const __nv_bfloat16*)d_in[2];
    const __nv_bfloat16* wqkv_b = (const __nv_bfloat16*)d_in[4];
    const __nv_bfloat16* wo_b = (const __nv_bfloat16*)d_in[5];
    const __nv_bfloat16* gate_w = (const __nv_bfloat16*)d_in[6];

    void* fnp = nullptr;
    cudaDriverEntryPointQueryResult qr;
    cudaGetDriverEntryPoint("cuTensorMapEncodeTiled", &fnp, cudaEnableDefault, &qr);
    EncodeFn enc = (EncodeFn)fnp;
    void* qkv = nullptr;
    cudaGetSymbolAddress(&qkv, g_qkv);

    CUtensorMap tmX, tmWb, tmWa, tmS;
    {
        const cuuint64_t d[4] = {640, 8, 2, 128}, s[3] = {2560, 1280, 20480};
        const cuuint32_t b[4] = {64, 8, 2, 8};
        make_map(enc, &tmX, x, 4, d, s, b, CU_TENSOR_MAP_SWIZZLE_128B);
    }
    {
        const cuuint64_t d[3] = {240, 8, 640}, s[2] = {480, 3840};
        const cuuint32_t b[3] = {64, 1, 32};
        make_map(enc, &tmWb, wqkv_b, 3, d, s, b, CU_TENSOR_MAP_SWIZZLE_128B);
        make_map(enc, &tmWa, wqkv_a, 3, d, s, b, CU_TENSOR_MAP_SWIZZLE_128B);
    }
    {
        const cuuint64_t d[3] = {192, 256, 192}, s[2] = {384, (cuuint64_t)HEAD_BYTES};
        const cuuint32_t b[3] = {192, 16, 12};
        make_map(enc, &tmS, qkv, 3, d, s, b, CU_TENSOR_MAP_SWIZZLE_NONE);
    }
    cudaFuncSetAttribute(k_fused, cudaFuncAttributeMaxDynamicSharedMemorySize, SMEM_BYTES);
    k_fused<<<128, 512, SMEM_BYTES, cudaStreamPerThread>>>(tmX, tmWb, tmWa, tmS, x, gate_w,
                                                          (const uint8_t*)wo_a, (const uint8_t*)wo_b, (__nv_bfloat16*)d_out);
}
```

```cpp
#include <cuda_runtime.h>
#include <cuda_bf16.h>
#include <cuda.h>
#include <stdint.h>

namespace {

constexpr int SEQ = 2048, DM = 640;
constexpr int HEAD_BYTES = 256 * 384;
#define POLYM 0xddddu
constexpr uint32_t POLY16 = POLYM;
constexpr float QSCALE = 0.22360679774997896f * 1.4426950408889634f;

__device__ __align__(1024) uint8_t g_qkv[2 * 96 * HEAD_BYTES];
__device__ __align__(128) float g_gate[SEQ];
__device__ __align__(128) float g_nrm[16 * 96];
enum { F_QKVB = 0, F_QKVA = 8, F_HELP = 16, F_EXIT = 17, F_ATTA = 18, F_ATTB = 26, F_COUNT = 58 };
__device__ uint32_t g_flag[F_COUNT * 32];
__device__ __align__(1024) uint4 g_wo[8 * 160 * 10 * 8];
__device__ __align__(1024) uint2 g_att[32 * 160 * 128];

#define TR(i, cond)
#define TRINIT()
#define TRFLUSH()
#define TR2(i, c) TR(i, c)
__device__ __forceinline__ uint32_t smem_u32(const void* p) { return (uint32_t)__cvta_generic_to_shared(p); }
__device__ __forceinline__ void mbar_init(uint32_t bar, int cnt) { asm volatile("mbarrier.init.shared::cta.b64 [%0], %1;" ::"r"(bar), "r"(cnt) : "memory"); }
__device__ __forceinline__ void mbar_expect_tx(uint32_t bar, int bytes) { asm volatile("mbarrier.arrive.expect_tx.shared::cta.b64 _, [%0], %1;" ::"r"(bar), "r"(bytes) : "memory"); }
__device__ __forceinline__ void mbar_arrive(uint32_t bar) { asm volatile("mbarrier.arrive.shared::cta.b64 _, [%0];" ::"r"(bar) : "memory"); }
__device__ __forceinline__ bool mbar_try(uint32_t bar, uint32_t parity) {
    uint32_t ok;
    asm volatile("{\n.reg .pred p;\nmbarrier.try_wait.parity.shared::cta.b64 p, [%1], %2;\nselp.u32 %0, 1, 0, p;\n}\n" : "=r"(ok) : "r"(bar), "r"(parity) : "memory");
    return ok;
}
__device__ __forceinline__ void mbar_wait(uint32_t bar, uint32_t parity) {
    if (mbar_try(bar, parity)) return;
#pragma unroll 1
    for (int i = 0; i < (1 << 21); i++)
        if (mbar_try(bar, parity)) return;
    __trap();
}
__device__ __forceinline__ void fence_mbar_init() { asm volatile("fence.mbarrier_init.release.cluster;" ::: "memory"); }
__device__ __forceinline__ void tma_x(uint32_t dst, const CUtensorMap* tm, int k, int blk16, uint32_t bar) {
    asm volatile("cp.async.bulk.tensor.4d.shared::cluster.global.mbarrier::complete_tx::bytes [%0], [%1, {%2, %5, %5, %3}], [%4];"
                 ::"r"(dst), "l"(tm), "r"(k), "r"(blk16), "r"(bar), "r"(0) : "memory");
}
__device__ __forceinline__ void tma_3d_mc(uint32_t dst, const CUtensorMap* tm, int c0, int c1, int c2, uint32_t bar, uint16_t mask) {
    asm volatile("cp.async.bulk.tensor.3d.shared::cluster.global.mbarrier::complete_tx::bytes.multicast::cluster [%0], [%1, {%2, %3, %4}], [%5], %6;"
                 ::"r"(dst), "l"(tm), "r"(c0), "r"(c1), "r"(c2), "r"(bar), "h"(mask) : "memory");
}
__device__ __forceinline__ void mbar_arrive_cluster(uint32_t bar, uint32_t cta) {
    asm volatile("{\n.reg .b32 ra;\nmapa.shared::cluster.u32 ra, %0, %1;\nmbarrier.arrive.shared::cluster.b64 _, [ra];\n}\n" ::"r"(bar), "r"(cta) : "memory");
}
__device__ __forceinline__ void tma_store_3d(const CUtensorMap* tm, uint32_t src, int c0, int c1, int c2) {
    asm volatile("cp.async.bulk.tensor.3d.global.shared::cta.bulk_group [%0, {%2, %3, %4}], [%1];" ::"l"(tm), "r"(src), "r"(c0), "r"(c1), "r"(c2) : "memory");
}
__device__ __forceinline__ void cluster_arrive() { asm volatile("barrier.cluster.arrive.relaxed.aligned;" ::: "memory"); }
__device__ __forceinline__ void cluster_wait() { asm volatile("barrier.cluster.wait.aligned;" ::: "memory"); }
__device__ __forceinline__ void named_sync(int id, int n) { asm volatile("bar.sync %0, %1;" ::"r"(id), "r"(n) : "memory"); }
__device__ __forceinline__ void flag_add_done(uint32_t* p) {
    asm volatile("fence.proxy.async.global;\nred.release.gpu.global.add.u32 [%0], 1;" ::"l"(p) : "memory");
}
__device__ __forceinline__ void flag_wait(const uint32_t* p, uint32_t target) {
#pragma unroll 1
    for (int i = 0; i < (1 << 22); i++) {
        uint32_t v;
        asm volatile("ld.acquire.gpu.global.u32 %0, [%1];" : "=r"(v) : "l"(p) : "memory");
        if (v >= target) return;
        __nanosleep(20);
    }
    __trap();
}
__device__ __forceinline__ void flag_wait_fast(const uint32_t* p, uint32_t target) {
    uint32_t v0, v1, v2;
    asm volatile("ld.relaxed.gpu.global.u32 %0, [%1];" : "=r"(v0) : "l"(p) : "memory");
    __nanosleep(100);
    asm volatile("ld.relaxed.gpu.global.u32 %0, [%1];" : "=r"(v1) : "l"(p) : "memory");
    __nanosleep(100);
#pragma unroll 1
    for (int i = 0; i < (1 << 22); i++) {
        asm volatile("ld.relaxed.gpu.global.u32 %0, [%1];" : "=r"(v2) : "l"(p) : "memory");
        if (v0 >= target) break;
        asm volatile("ld.relaxed.gpu.global.u32 %0, [%1];" : "=r"(v0) : "l"(p) : "memory");
        if (v1 >= target) break;
        asm volatile("ld.relaxed.gpu.global.u32 %0, [%1];" : "=r"(v1) : "l"(p) : "memory");
        if (v2 >= target) break;
        if (i == (1 << 22) - 1) __trap();
    }
    asm volatile("fence.acquire.gpu;" ::: "memory");
}
__device__ __forceinline__ void flag_wait_head(const uint32_t* base, int h, uint32_t help_target) {
    const uint32_t *p0 = base + (h / 12) * 32, *p1 = base + ((32 + h) / 12) * 32, *p2 = base + ((64 + h) / 12) * 32;
    const uint32_t target = 16;
#pragma unroll 1
    for (int i = 0; i < (1 << 22); i++) {
        uint32_t v0, v1, v2, v3;
        asm volatile("ld.relaxed.gpu.global.u32 %0, [%1];" : "=r"(v3) : "l"(g_flag + F_HELP * 32) : "memory");
        asm volatile("ld.relaxed.gpu.global.u32 %0, [%1];" : "=r"(v0) : "l"(p0) : "memory");
        asm volatile("ld.relaxed.gpu.global.u32 %0, [%1];" : "=r"(v1) : "l"(p1) : "memory");
        asm volatile("ld.relaxed.gpu.global.u32 %0, [%1];" : "=r"(v2) : "l"(p2) : "memory");
        if (v0 >= target && v1 >= target && v2 >= target && v3 >= help_target) { asm volatile("fence.acquire.gpu;" ::: "memory"); return; }
        __nanosleep(40);
    }
    __trap();
}
__device__ __forceinline__ uint32_t ld_relaxed(const uint32_t* p) { uint32_t v; asm volatile("ld.relaxed.gpu.global.u32 %0, [%1];" : "=r"(v) : "l"(p) : "memory"); return v; }
__device__ __forceinline__ float ldcg_f32(const float* p) { float v; asm volatile("ld.global.cg.f32 %0, [%1];" : "=f"(v) : "l"(p) : "memory"); return v; }
__device__ __forceinline__ uint32_t ldcg_u32(const void* p) { uint32_t v; asm volatile("ld.global.cg.b32 %0, [%1];" : "=r"(v) : "l"(p) : "memory"); return v; }
__device__ __forceinline__ void bulk_g2s(uint32_t dst, const void* src, int bytes, uint32_t bar) {
    asm volatile("fence.proxy.async.global;\ncp.async.bulk.shared::cluster.global.mbarrier::complete_tx::bytes [%0], [%1], %2, [%3];"
                 ::"r"(dst), "l"(src), "r"(bytes), "r"(bar) : "memory");
}
__device__ __forceinline__ void bulk_s2g(void* dst, uint32_t src, int bytes) {
    asm volatile("cp.async.bulk.global.shared::cta.bulk_group [%0], [%1], %2;" ::"l"(dst), "r"(src), "r"(bytes) : "memory");
}
__device__ __forceinline__ void bulk_commit() { asm volatile("cp.async.bulk.commit_group;" ::: "memory"); }
__device__ __forceinline__ void bulk_wait_all() { asm volatile("cp.async.bulk.wait_group 0;" ::: "memory"); }
__device__ __forceinline__ void fence_async_smem() { asm volatile("fence.proxy.async.shared::cta;" ::: "memory"); }
__device__ __forceinline__ void stsm4(uint32_t a, uint32_t r0, uint32_t r1, uint32_t r2, uint32_t r3) {
    asm volatile("stmatrix.sync.aligned.m8n8.x4.shared.b16 [%0], {%1,%2,%3,%4};" ::"r"(a), "r"(r0), "r"(r1), "r"(r2), "r"(r3) : "memory");
}
__device__ __forceinline__ void prefetch_tmap(const CUtensorMap* tm) { asm volatile("prefetch.tensormap [%0];" ::"l"(tm) : "memory"); }
__device__ __forceinline__ void wg_fence() { asm volatile("wgmma.fence.sync.aligned;" ::: "memory"); }
__device__ __forceinline__ void wg_commit() { asm volatile("wgmma.commit_group.sync.aligned;" ::: "memory"); }
template <int N> __device__ __forceinline__ void wg_wait() { asm volatile("wgmma.wait_group.sync.aligned %0;" ::"n"(N) : "memory"); }
__device__ __forceinline__ uint64_t mkdesc(uint32_t addr, uint32_t lbo, uint32_t sbo, uint32_t swz) {
    return (uint64_t)((addr & 0x3FFFF) >> 4) | ((uint64_t)(lbo >> 4) << 16) | ((uint64_t)(sbo >> 4) << 32) | ((uint64_t)swz << 62);
}
template <int N> __device__ __forceinline__ void pin(float (&r)[N]) {
#pragma unroll
    for (int i = 0; i < N; i++) asm volatile("" : "+f"(r[i])::"memory");
}
template <int N> __device__ __forceinline__ void pin(uint32_t (&r)[N]) {
#pragma unroll
    for (int i = 0; i < N; i++) asm volatile("" : "+r"(r[i])::"memory");
}
__device__ __forceinline__ float ex2(float x) { float y; asm("ex2.approx.ftz.f32 %0, %1;" : "=f"(y) : "f"(x)); return y; }
__device__ __forceinline__ uint32_t pack2(float lo, float hi) { uint32_t r; asm("cvt.rn.bf16x2.f32 %0, %1, %2;" : "=r"(r) : "f"(hi), "f"(lo)); return r; }
__device__ __forceinline__ uint32_t hfma2(uint32_t a, uint32_t b, uint32_t c) { uint32_t d; asm("fma.rn.bf16x2 %0, %1, %2, %3;" : "=r"(d) : "r"(a), "r"(b), "r"(c)); return d; }
__device__ __forceinline__ float bf_lo(uint32_t v) { return __uint_as_float(v << 16); }
__device__ __forceinline__ float bf_hi(uint32_t v) { return __uint_as_float(v & 0xffff0000u); }
__device__ __forceinline__ void mma16816(float (&c)[4], uint32_t a0, uint32_t a1, uint32_t a2, uint32_t a3, uint32_t b0, uint32_t b1) {
    asm volatile("mma.sync.aligned.m16n8k16.row.col.f32.bf16.bf16.f32 {%0,%1,%2,%3}, {%4,%5,%6,%7}, {%8,%9}, {%0,%1,%2,%3};"
                 : "+f"(c[0]), "+f"(c[1]), "+f"(c[2]), "+f"(c[3]) : "r"(a0), "r"(a1), "r"(a2), "r"(a3), "r"(b0), "r"(b1));
}
__device__ __forceinline__ void mma1688(float (&c)[4], uint32_t a0, uint32_t a1, uint32_t b0) {
    asm volatile("mma.sync.aligned.m16n8k8.row.col.f32.bf16.bf16.f32 {%0,%1,%2,%3}, {%4,%5}, {%6}, {%0,%1,%2,%3};"
                 : "+f"(c[0]), "+f"(c[1]), "+f"(c[2]), "+f"(c[3]) : "r"(a0), "r"(a1), "r"(b0));
}
__device__ __forceinline__ uint32_t movm_t(uint32_t a) { uint32_t d; asm volatile("movmatrix.sync.aligned.m8n8.trans.b16 %0, %1;" : "=r"(d) : "r"(a)); return d; }
__device__ __forceinline__ void stg128(void* p, uint4 v) { asm volatile("st.global.v4.b32 [%0], {%1,%2,%3,%4};" ::"l"(p), "r"(v.x), "r"(v.y), "r"(v.z), "r"(v.w) : "memory"); }
__device__ __forceinline__ void stg64(void* p, uint32_t a, uint32_t b) { asm volatile("st.global.v2.b32 [%0], {%1,%2};" ::"l"(p), "r"(a), "r"(b) : "memory"); }
__device__ __forceinline__ int frag_pos(int warp4, int lane) { return ((lane & 2) << 5) | (warp4 << 4) | ((lane >> 2) << 1) | (lane & 1); }
__device__ __forceinline__ bool elect_one() {
    uint32_t p;
    asm volatile("{\n.reg .pred p;\nelect.sync _|p, 0xffffffff;\nselp.u32 %0, 1, 0, p;\n}\n" : "=r"(p));
    return p;
}
__device__ __forceinline__ uint32_t clock_lo() { uint32_t v; asm volatile("mov.u32 %0, %%clock;" : "=r"(v)); return v; }
__device__ __forceinline__ int fresh_bid() { int v; asm volatile("mov.u32 %0, %%ctaid.x;" : "=r"(v)); return v; }
__device__ __forceinline__ int fresh_wid() { int v; asm volatile("mov.u32 %0, %%tid.x;" : "=r"(v)); return __shfl_sync(0xffffffffu, v >> 5, 0); }
__device__ __forceinline__ int here(int v) { asm volatile("" : "+r"(v)); return v; }
__device__ __forceinline__ int fresh_tid() { int v; asm volatile("mov.u32 %0, %%tid.x;" : "=r"(v)); return v; }
__device__ __forceinline__ uint32_t lds32(uint32_t a) { uint32_t v; asm volatile("ld.shared.b32 %0, [%1];" : "=r"(v) : "r"(a) : "memory"); return v; }
__device__ __forceinline__ uint4 lds128(uint32_t a) { uint4 v; asm volatile("ld.shared.v4.b32 {%0,%1,%2,%3}, [%4];" : "=r"(v.x), "=r"(v.y), "=r"(v.z), "=r"(v.w) : "r"(a)); return v; }

__device__ __forceinline__ void wgmma_ss128(float (&d)[64], uint64_t da, uint64_t db, int sd) {
    asm volatile("{\n.reg .pred p;\nsetp.ne.b32 p, %66, 0;\n"
        "wgmma.mma_async.sync.aligned.m64n128k16.f32.bf16.bf16 "
        "{%0,%1,%2,%3,%4,%5,%6,%7,%8,%9,%10,%11,%12,%13,%14,%15,%16,%17,%18,%19,"
        "%20,%21,%22,%23,%24,%25,%26,%27,%28,%29,%30,%31,%32,%33,%34,%35,%36,%37,%38,%39,"
        "%40,%41,%42,%43,%44,%45,%46,%47,%48,%49,%50,%51,%52,%53,%54,%55,%56,%57,%58,%59,"
        "%60,%61,%62,%63}, "
        "%64, %65, p, 1, 1, 0, 1;\n}\n"
        : "+f"(d[0]), "+f"(d[1]), "+f"(d[2]), "+f"(d[3]), "+f"(d[4]), "+f"(d[5]), "+f"(d[6]), "+f"(d[7]), "+f"(d[8]), "+f"(d[9]),
          "+f"(d[10]), "+f"(d[11]), "+f"(d[12]), "+f"(d[13]), "+f"(d[14]), "+f"(d[15]), "+f"(d[16]), "+f"(d[17]), "+f"(d[18]), "+f"(d[19]),
          "+f"(d[20]), "+f"(d[21]), "+f"(d[22]), "+f"(d[23]), "+f"(d[24]), "+f"(d[25]), "+f"(d[26]), "+f"(d[27]), "+f"(d[28]), "+f"(d[29]),
          "+f"(d[30]), "+f"(d[31]), "+f"(d[32]), "+f"(d[33]), "+f"(d[34]), "+f"(d[35]), "+f"(d[36]), "+f"(d[37]), "+f"(d[38]), "+f"(d[39]),
          "+f"(d[40]), "+f"(d[41]), "+f"(d[42]), "+f"(d[43]), "+f"(d[44]), "+f"(d[45]), "+f"(d[46]), "+f"(d[47]), "+f"(d[48]), "+f"(d[49]),
          "+f"(d[50]), "+f"(d[51]), "+f"(d[52]), "+f"(d[53]), "+f"(d[54]), "+f"(d[55]), "+f"(d[56]), "+f"(d[57]), "+f"(d[58]), "+f"(d[59]),
          "+f"(d[60]), "+f"(d[61]), "+f"(d[62]), "+f"(d[63])
        : "l"(da), "l"(db), "r"(sd));
}
__device__ __forceinline__ void wgmma_ss112(float (&d)[56], uint64_t da, uint64_t db, int sd) {
    asm volatile("{\n.reg .pred p;\nsetp.ne.b32 p, %58, 0;\n"
        "wgmma.mma_async.sync.aligned.m64n112k16.f32.bf16.bf16 "
        "{%0,%1,%2,%3,%4,%5,%6,%7,%8,%9,%10,%11,%12,%13,%14,%15,%16,%17,%18,%19,"
        "%20,%21,%22,%23,%24,%25,%26,%27,%28,%29,%30,%31,%32,%33,%34,%35,%36,%37,%38,%39,"
        "%40,%41,%42,%43,%44,%45,%46,%47,%48,%49,%50,%51,%52,%53,%54,%55}, "
        "%56, %57, p, 1, 1, 0, 1;\n}\n"
        : "+f"(d[0]), "+f"(d[1]), "+f"(d[2]), "+f"(d[3]), "+f"(d[4]), "+f"(d[5]), "+f"(d[6]), "+f"(d[7]), "+f"(d[8]), "+f"(d[9]),
          "+f"(d[10]), "+f"(d[11]), "+f"(d[12]), "+f"(d[13]), "+f"(d[14]), "+f"(d[15]), "+f"(d[16]), "+f"(d[17]), "+f"(d[18]), "+f"(d[19]),
          "+f"(d[20]), "+f"(d[21]), "+f"(d[22]), "+f"(d[23]), "+f"(d[24]), "+f"(d[25]), "+f"(d[26]), "+f"(d[27]), "+f"(d[28]), "+f"(d[29]),
          "+f"(d[30]), "+f"(d[31]), "+f"(d[32]), "+f"(d[33]), "+f"(d[34]), "+f"(d[35]), "+f"(d[36]), "+f"(d[37]), "+f"(d[38]), "+f"(d[39]),
          "+f"(d[40]), "+f"(d[41]), "+f"(d[42]), "+f"(d[43]), "+f"(d[44]), "+f"(d[45]), "+f"(d[46]), "+f"(d[47]), "+f"(d[48]), "+f"(d[49]),
          "+f"(d[50]), "+f"(d[51]), "+f"(d[52]), "+f"(d[53]), "+f"(d[54]), "+f"(d[55])
        : "l"(da), "l"(db), "r"(sd));
}
__device__ __forceinline__ void wgmma_rs80(float (&d)[40], uint32_t a0, uint32_t a1, uint32_t a2, uint32_t a3, uint64_t db) {
    asm volatile("{\n.reg .pred p;\nsetp.eq.b32 p, 0, 0;\n"
        "wgmma.mma_async.sync.aligned.m64n80k16.f32.bf16.bf16 "
        "{%0,%1,%2,%3,%4,%5,%6,%7,%8,%9,%10,%11,%12,%13,%14,%15,%16,%17,%18,%19,"
        "%20,%21,%22,%23,%24,%25,%26,%27,%28,%29,%30,%31,%32,%33,%34,%35,%36,%37,%38,%39}, "
        "{%40,%41,%42,%43}, %44, p, 1, 1, 1;\n}\n"
        : "+f"(d[0]), "+f"(d[1]), "+f"(d[2]), "+f"(d[3]), "+f"(d[4]), "+f"(d[5]), "+f"(d[6]), "+f"(d[7]), "+f"(d[8]), "+f"(d[9]),
          "+f"(d[10]), "+f"(d[11]), "+f"(d[12]), "+f"(d[13]), "+f"(d[14]), "+f"(d[15]), "+f"(d[16]), "+f"(d[17]), "+f"(d[18]), "+f"(d[19]),
          "+f"(d[20]), "+f"(d[21]), "+f"(d[22]), "+f"(d[23]), "+f"(d[24]), "+f"(d[25]), "+f"(d[26]), "+f"(d[27]), "+f"(d[28]), "+f"(d[29]),
          "+f"(d[30]), "+f"(d[31]), "+f"(d[32]), "+f"(d[33]), "+f"(d[34]), "+f"(d[35]), "+f"(d[36]), "+f"(d[37]), "+f"(d[38]), "+f"(d[39])
        : "r"(a0), "r"(a1), "r"(a2), "r"(a3), "l"(db));
}
__device__ __forceinline__ void wgmma_rs80f(float (&d)[40], uint32_t a0, uint32_t a1, uint32_t a2, uint32_t a3, uint64_t db) {
    asm volatile("{\n.reg .pred p;\nsetp.ne.b32 p, 0, 0;\n"
        "wgmma.mma_async.sync.aligned.m64n80k16.f32.bf16.bf16 "
        "{%0,%1,%2,%3,%4,%5,%6,%7,%8,%9,%10,%11,%12,%13,%14,%15,%16,%17,%18,%19,"
        "%20,%21,%22,%23,%24,%25,%26,%27,%28,%29,%30,%31,%32,%33,%34,%35,%36,%37,%38,%39}, "
        "{%40,%41,%42,%43}, %44, p, 1, 1, 1;\n}\n"
        : "=f"(d[0]), "=f"(d[1]), "=f"(d[2]), "=f"(d[3]), "=f"(d[4]), "=f"(d[5]), "=f"(d[6]), "=f"(d[7]), "=f"(d[8]), "=f"(d[9]),
          "=f"(d[10]), "=f"(d[11]), "=f"(d[12]), "=f"(d[13]), "=f"(d[14]), "=f"(d[15]), "=f"(d[16]), "=f"(d[17]), "=f"(d[18]), "=f"(d[19]),
          "=f"(d[20]), "=f"(d[21]), "=f"(d[22]), "=f"(d[23]), "=f"(d[24]), "=f"(d[25]), "=f"(d[26]), "=f"(d[27]), "=f"(d[28]), "=f"(d[29]),
          "=f"(d[30]), "=f"(d[31]), "=f"(d[32]), "=f"(d[33]), "=f"(d[34]), "=f"(d[35]), "=f"(d[36]), "=f"(d[37]), "=f"(d[38]), "=f"(d[39])
        : "r"(a0), "r"(a1), "r"(a2), "r"(a3), "l"(db));
}
__device__ __forceinline__ void wgmma_qk0(float (&d)[32], uint32_t a0, uint32_t a1, uint32_t a2, uint32_t a3, uint64_t db) {
    asm volatile("{\n.reg .pred p;\nsetp.ne.b32 p, 0, 0;\n"
        "wgmma.mma_async.sync.aligned.m64n64k16.f32.bf16.bf16 "
        "{%0,%1,%2,%3,%4,%5,%6,%7,%8,%9,%10,%11,%12,%13,%14,%15,%16,%17,%18,%19,"
        "%20,%21,%22,%23,%24,%25,%26,%27,%28,%29,%30,%31}, "
        "{%32,%33,%34,%35}, %36, p, 1, 1, 0;\n}\n"
        : "=f"(d[0]), "=f"(d[1]), "=f"(d[2]), "=f"(d[3]), "=f"(d[4]), "=f"(d[5]), "=f"(d[6]), "=f"(d[7]), "=f"(d[8]), "=f"(d[9]),
          "=f"(d[10]), "=f"(d[11]), "=f"(d[12]), "=f"(d[13]), "=f"(d[14]), "=f"(d[15]), "=f"(d[16]), "=f"(d[17]), "=f"(d[18]), "=f"(d[19]),
          "=f"(d[20]), "=f"(d[21]), "=f"(d[22]), "=f"(d[23]), "=f"(d[24]), "=f"(d[25]), "=f"(d[26]), "=f"(d[27]), "=f"(d[28]), "=f"(d[29]),
          "=f"(d[30]), "=f"(d[31])
        : "r"(a0), "r"(a1), "r"(a2), "r"(a3), "l"(db));
}
__device__ __forceinline__ void wgmma_qk1(float (&d)[32], uint32_t a0, uint32_t a1, uint32_t a2, uint32_t a3, uint64_t db) {
    asm volatile("{\n.reg .pred p;\nsetp.eq.b32 p, 0, 0;\n"
        "wgmma.mma_async.sync.aligned.m64n64k16.f32.bf16.bf16 "
        "{%0,%1,%2,%3,%4,%5,%6,%7,%8,%9,%10,%11,%12,%13,%14,%15,%16,%17,%18,%19,"
        "%20,%21,%22,%23,%24,%25,%26,%27,%28,%29,%30,%31}, "
        "{%32,%33,%34,%35}, %36, p, 1, 1, 0;\n}\n"
        : "+f"(d[0]), "+f"(d[1]), "+f"(d[2]), "+f"(d[3]), "+f"(d[4]), "+f"(d[5]), "+f"(d[6]), "+f"(d[7]), "+f"(d[8]), "+f"(d[9]),
          "+f"(d[10]), "+f"(d[11]), "+f"(d[12]), "+f"(d[13]), "+f"(d[14]), "+f"(d[15]), "+f"(d[16]), "+f"(d[17]), "+f"(d[18]), "+f"(d[19]),
          "+f"(d[20]), "+f"(d[21]), "+f"(d[22]), "+f"(d[23]), "+f"(d[24]), "+f"(d[25]), "+f"(d[26]), "+f"(d[27]), "+f"(d[28]), "+f"(d[29]),
          "+f"(d[30]), "+f"(d[31])
        : "r"(a0), "r"(a1), "r"(a2), "r"(a3), "l"(db));
}
__device__ __forceinline__ void wgmma_pv(float (&d)[12], uint32_t a0, uint32_t a1, uint32_t a2, uint32_t a3, uint64_t db) {
    asm volatile("{\n.reg .pred p;\nsetp.eq.b32 p, 0, 0;\n"
        "wgmma.mma_async.sync.aligned.m64n24k16.f32.bf16.bf16 "
        "{%0,%1,%2,%3,%4,%5,%6,%7,%8,%9,%10,%11}, "
        "{%12,%13,%14,%15}, %16, p, 1, 1, 1;\n}\n"
        : "+f"(d[0]), "+f"(d[1]), "+f"(d[2]), "+f"(d[3]), "+f"(d[4]), "+f"(d[5]), "+f"(d[6]), "+f"(d[7]), "+f"(d[8]), "+f"(d[9]),
          "+f"(d[10]), "+f"(d[11])
        : "r"(a0), "r"(a1), "r"(a2), "r"(a3), "l"(db));
}
__device__ __forceinline__ void wgmma_pvn(float (&d)[12], uint32_t a0, uint32_t a1, uint32_t a2, uint32_t a3, uint64_t db) {
    asm volatile("{\n.reg .pred p;\nsetp.eq.b32 p, 0, 0;\n"
        "wgmma.mma_async.sync.aligned.m64n24k16.f32.bf16.bf16 "
        "{%0,%1,%2,%3,%4,%5,%6,%7,%8,%9,%10,%11}, "
        "{%12,%13,%14,%15}, %16, p, -1, 1, 1;\n}\n"
        : "+f"(d[0]), "+f"(d[1]), "+f"(d[2]), "+f"(d[3]), "+f"(d[4]), "+f"(d[5]), "+f"(d[6]), "+f"(d[7]), "+f"(d[8]), "+f"(d[9]),
          "+f"(d[10]), "+f"(d[11])
        : "r"(a0), "r"(a1), "r"(a2), "r"(a3), "l"(db));
}
__device__ __forceinline__ void wgmma_pv0(float (&d)[12], uint32_t a0, uint32_t a1, uint32_t a2, uint32_t a3, uint64_t db) {
    asm volatile("{\n.reg .pred p;\nsetp.ne.b32 p, 0, 0;\n"
        "wgmma.mma_async.sync.aligned.m64n24k16.f32.bf16.bf16 "
        "{%0,%1,%2,%3,%4,%5,%6,%7,%8,%9,%10,%11}, "
        "{%12,%13,%14,%15}, %16, p, 1, 1, 1;\n}\n"
        : "=f"(d[0]), "=f"(d[1]), "=f"(d[2]), "=f"(d[3]), "=f"(d[4]), "=f"(d[5]), "=f"(d[6]), "=f"(d[7]), "=f"(d[8]), "=f"(d[9]),
          "=f"(d[10]), "=f"(d[11])
        : "r"(a0), "r"(a1), "r"(a2), "r"(a3), "l"(db));
}
__device__ __forceinline__ void wgmma_l64a(float (&d)[32], uint64_t da, uint64_t db) {
    asm volatile("{\n.reg .pred p;\nsetp.ne.b32 p, 0, 0;\n"
        "wgmma.mma_async.sync.aligned.m64n64k16.f32.bf16.bf16 "
        "{%0,%1,%2,%3,%4,%5,%6,%7,%8,%9,%10,%11,%12,%13,%14,%15,%16,%17,%18,%19,"
        "%20,%21,%22,%23,%24,%25,%26,%27,%28,%29,%30,%31}, "
        "%32, %33, p, 1, 1, 0, 0;\n}\n"
        : "=f"(d[0]), "=f"(d[1]), "=f"(d[2]), "=f"(d[3]), "=f"(d[4]), "=f"(d[5]), "=f"(d[6]), "=f"(d[7]), "=f"(d[8]), "=f"(d[9]),
          "=f"(d[10]), "=f"(d[11]), "=f"(d[12]), "=f"(d[13]), "=f"(d[14]), "=f"(d[15]), "=f"(d[16]), "=f"(d[17]), "=f"(d[18]), "=f"(d[19]),
          "=f"(d[20]), "=f"(d[21]), "=f"(d[22]), "=f"(d[23]), "=f"(d[24]), "=f"(d[25]), "=f"(d[26]), "=f"(d[27]), "=f"(d[28]), "=f"(d[29]),
          "=f"(d[30]), "=f"(d[31])
        : "l"(da), "l"(db));
}
__device__ __forceinline__ void wgmma_l64b(float (&d)[32], uint64_t da, uint64_t db) {
    asm volatile("{\n.reg .pred p;\nsetp.eq.b32 p, 0, 0;\n"
        "wgmma.mma_async.sync.aligned.m64n64k16.f32.bf16.bf16 "
        "{%0,%1,%2,%3,%4,%5,%6,%7,%8,%9,%10,%11,%12,%13,%14,%15,%16,%17,%18,%19,"
        "%20,%21,%22,%23,%24,%25,%26,%27,%28,%29,%30,%31}, "
        "%32, %33, p, 1, 1, 0, 0;\n}\n"
        : "+f"(d[0]), "+f"(d[1]), "+f"(d[2]), "+f"(d[3]), "+f"(d[4]), "+f"(d[5]), "+f"(d[6]), "+f"(d[7]), "+f"(d[8]), "+f"(d[9]),
          "+f"(d[10]), "+f"(d[11]), "+f"(d[12]), "+f"(d[13]), "+f"(d[14]), "+f"(d[15]), "+f"(d[16]), "+f"(d[17]), "+f"(d[18]), "+f"(d[19]),
          "+f"(d[20]), "+f"(d[21]), "+f"(d[22]), "+f"(d[23]), "+f"(d[24]), "+f"(d[25]), "+f"(d[26]), "+f"(d[27]), "+f"(d[28]), "+f"(d[29]),
          "+f"(d[30]), "+f"(d[31])
        : "l"(da), "l"(db));
}
__device__ __forceinline__ void wgmma_l16a(float (&d)[8], uint64_t da, uint64_t db) {
    asm volatile("{\n.reg .pred p;\nsetp.ne.b32 p, 0, 0;\n"
        "wgmma.mma_async.sync.aligned.m64n16k16.f32.bf16.bf16 "
        "{%0,%1,%2,%3,%4,%5,%6,%7}, "
        "%8, %9, p, 1, 1, 0, 0;\n}\n"
        : "=f"(d[0]), "=f"(d[1]), "=f"(d[2]), "=f"(d[3]), "=f"(d[4]), "=f"(d[5]), "=f"(d[6]), "=f"(d[7])
        : "l"(da), "l"(db));
}
__device__ __forceinline__ void wgmma_l16b(float (&d)[8], uint64_t da, uint64_t db) {
    asm volatile("{\n.reg .pred p;\nsetp.eq.b32 p, 0, 0;\n"
        "wgmma.mma_async.sync.aligned.m64n16k16.f32.bf16.bf16 "
        "{%0,%1,%2,%3,%4,%5,%6,%7}, "
        "%8, %9, p, 1, 1, 0, 0;\n}\n"
        : "+f"(d[0]), "+f"(d[1]), "+f"(d[2]), "+f"(d[3]), "+f"(d[4]), "+f"(d[5]), "+f"(d[6]), "+f"(d[7])
        : "l"(da), "l"(db));
}

__device__ __forceinline__ uint32_t exp2_pair_fma(float a, float b) {
    const uint32_t y = __byte_perm(__float_as_uint(a), __float_as_uint(b), 0x6521);
    const uint32_t z = 0xFE7BFE7Bu - y;
    const uint32_t e = hfma2(y, z, 0x3F053F05u);
    return hfma2(y, e, y);
}
__device__ __forceinline__ void exp_tile(const float (&s)[32], uint32_t (&p)[16], const int MASK) {
#pragma unroll
    for (int j = 0; j < 8; j++) {
        if ((MASK >> (j >> 1)) & 1) { p[2 * j] = exp2_pair_fma(s[4 * j], s[4 * j + 1]); p[2 * j + 1] = exp2_pair_fma(s[4 * j + 2], s[4 * j + 3]); }
        else { p[2 * j] = pack2(ex2(s[4 * j]), ex2(s[4 * j + 1])); p[2 * j + 1] = pack2(ex2(s[4 * j + 2]), ex2(s[4 * j + 3])); }
    }
}
__device__ __forceinline__ void qk_tile(float (&s)[32], const uint32_t (&q)[8], uint64_t dk0, uint64_t dk1) {
    wgmma_qk0(s, q[0], q[1], q[2], q[3], dk0);
    wgmma_qk1(s, q[4], q[5], q[6], q[7], dk1);
}
__device__ __forceinline__ void pv_tile(float (&o)[12], const uint32_t (&p)[16], uint64_t dv, int mask) {
#pragma unroll
    for (int k = 0; k < 4; k++) {
        if ((mask >> k) & 1) wgmma_pvn(o, p[4 * k], p[4 * k + 1], p[4 * k + 2], p[4 * k + 3], dv + k * 48);
        else wgmma_pv(o, p[4 * k], p[4 * k + 1], p[4 * k + 2], p[4 * k + 3], dv + k * 48);
    }
}
__device__ __forceinline__ void finish_o(const float (&o)[12], uint32_t (&w)[6], int odd, float g0, float g1, int lane, float& l0, float& l1) {
    const int src = (lane & ~3) | (odd ? 0 : 2);
    l0 = __shfl_sync(0xffffffffu, o[8], src);
    l1 = __shfl_sync(0xffffffffu, o[10], src);
    float r0, r1;
    asm("rcp.approx.ftz.f32 %0, %1;" : "=f"(r0) : "f"(l0));
    asm("rcp.approx.ftz.f32 %0, %1;" : "=f"(r1) : "f"(l1));
    const float f0 = g0 * r0, f1 = g1 * r1;
#pragma unroll
    for (int d = 0; d < 3; d++) { w[2 * d] = pack2(o[4 * d] * f0, o[4 * d + 1] * f0); w[2 * d + 1] = pack2(o[4 * d + 2] * f1, o[4 * d + 3] * f1); }
}
__device__ __forceinline__ void store_o(const uint32_t (&w)[6], int row16, int h, int gbase, int lane) {
    uint2* p = g_att + ((row16 >> 2) * 160 + gbase + 5 * (h >> 1)) * 128 + frag_pos(row16 & 3, lane);
    const int off = (h & 1) ? 3 * 128 : 0;
    stg64(p + off, w[0], w[1]);
    stg64(p + off + 128, w[2], w[3]);
    if (((lane & 3) >= 2) == ((h & 1) != 0)) stg64(p + 2 * 128, w[4], w[5]);
}

#define PACE 300u
#define PROMO CU_TENSOR_MAP_L2_PROMOTION_L2_256B
#define MAP 1
#define P1_NT(b) ((b) >> 4)
#define P1_MP(b) (((b) >> 1) & 7)
#define LJ 16
#define DEFER 5
#define FENCE2()
#define P1_NTA(nt) (((nt) + 3) & 7)
#define S3J 22
#define S3T 14
#define S1T 9
#define S4J 20
#define S4T 5
#define S1J 10
#define G1 500u
#define G2 1200u
#define PF 2
#define SAJ 4
constexpr int SLOT = 24576;
constexpr int OFF_X = 98304, OFF_R = 6 * SLOT, OFF_L = OFF_R - 1536, OFF_BAR = 9 * SLOT;
constexpr int OFF_F = OFF_BAR + 1024 + 128, SMEM_BYTES = OFF_F + 8192;
enum { B_FULL = 0, B_EMPTY = 48, B_STGB = 96, B_STGA = 104, B_RET = 112, B_NRM = 144, B_HLP = 152, B_KV = 160, B_HDR = 192, B_L = 200, B_WO = 208, B_XCH = 248, B_AF = 264, B_LD = 328, B_R26 = 336, B_AE = 344, B_W0 = 376, B_ZERO = 400, B_MISC = 416, B_PUB = 1024 };
__host__ __device__ constexpr int k_off(int j) {
    return j < 8 ? (7 + (j >> 2)) * SLOT + (j & 3) * 3072 : j == 8 ? OFF_R - 6144 : j < 20 ? 3 * SLOT + (j - 9) * 3072 : j < 26 ? 36864 + (j - 20) * 3072 : (j - 26) * 3072;
}
__host__ __device__ constexpr int v_off(int j) { return k_off(j) + (j < 8 ? 4 : j == 8 ? 1 : j < 20 ? 11 : 6) * 3072; }
__host__ __device__ constexpr int wo_off(int i) { return 3 * SLOT + (i < 7 ? i : i - 7) * 20480; }
__host__ __device__ constexpr int wo_bar(int i) { return i < 3 ? 0 : i < 7 ? 1 : i - 5; }
constexpr float SCORE_LIMIT2 = 118.f * 118.f;

__device__ __forceinline__ void load_kv(uint32_t sb, int h, int i, int j0, int n, int arm) {
    const uint32_t bar = sb + OFF_BAR + B_KV + 8 * i;
    if (arm) mbar_expect_tx(bar, arm * 6144);
    bulk_g2s(sb + k_off(j0), g_qkv + (size_t)(32 + h) * HEAD_BYTES + j0 * 3072, n * 3072, bar);
    bulk_g2s(sb + v_off(j0), g_qkv + (size_t)(64 + h) * HEAD_BYTES + j0 * 3072, n * 3072, bar);
}
__device__ __forceinline__ void load_wo(uint32_t sb, int seq, int n) {
    const uint32_t bar = sb + OFF_BAR + B_WO + 8 * wo_bar(seq);
    mbar_expect_tx(bar, n * 20480);
    bulk_g2s(sb + wo_off(seq), reinterpret_cast<const uint8_t*>(g_wo) + (blockIdx.x & 7) * 204800 + seq * 20480, n * 20480, bar);
}

__device__ __forceinline__ void local_attn(uint32_t sb, int wid) {
    const uint32_t sL = sb + OFF_L;
    const int tid = fresh_tid(), lane = tid & 31, g = lane >> 2, t2 = (lane & 3) * 2;
    const int wg = wid >> 2, w = wid & 3;
    const int bid = fresh_bid(), h = bid >> 2, qb = bid & 3;
    const float* gp = g_gate + qb * 512 + wg * 128 + w * 16 + g;
    const float gt[4] = {ldcg_f32(gp), ldcg_f32(gp + 8), ldcg_f32(gp + 64), ldcg_f32(gp + 72)};
    const bool cur0 = t2 <= g, cur1 = t2 < g;
    mbar_wait(sb + OFF_BAR + B_L, 0);
    float v0[4], v1[4];
    {
        const uint32_t tq = sL + wg * 6144;
        const uint64_t dq0 = mkdesc(tq, 128, 384, 0), dq1 = mkdesc(tq + 256, 0, 384, 0);
        float sa[2][32], sc[2][8];
        wg_fence();
#pragma unroll
        for (int b = 0; b < 2; b++) {
            wgmma_l64a(sa[b], dq0 + b * 192, dq0 + b * 192 + (24576 >> 4)); wgmma_l64b(sa[b], dq1 + b * 192, dq1 + b * 192 + (24576 >> 4));
            wgmma_l16a(sc[b], dq0 + b * 192, dq0 + b * 192 + (27648 >> 4)); wgmma_l16b(sc[b], dq1 + b * 192, dq1 + b * 192 + (27648 >> 4));
        }
        wg_commit(); wg_wait<0>(); pin(sa[0]); pin(sa[1]); pin(sc[0]); pin(sc[1]);
#define LS(B, BLK, R, E) ((BLK) < 4 ? sa[B][((BLK) * 8 + (R) * 6 + (E)) & 31] : sc[B][(R) * 6 + (E)])
#define LWIN(W) { _Pragma("unroll") for (int i = 0; i < 4; i++) { v0[i] = cur0 ? LS(i >> 1, (W) + 1, i & 1, 0) : LS(i >> 1, W, i & 1, 0); \
                                                                 v1[i] = cur1 ? LS(i >> 1, (W) + 1, i & 1, 1) : LS(i >> 1, W, i & 1, 1); } }
        if (w == 0) LWIN(0) else if (w == 1) LWIN(1) else if (w == 2) LWIN(2) else LWIN(3)
#undef LWIN
#undef LS
    }
    if (qb == 0 && wid == 0) {
        if (!cur0) v0[0] = v0[1] = -INFINITY;
        if (!cur1) v1[0] = v1[1] = -INFINITY;
    }
    float m[4], l[4];
#pragma unroll
    for (int i = 0; i < 4; i++) m[i] = fmaxf(v0[i], v1[i]);
#pragma unroll
    for (int i = 0; i < 4; i++) m[i] = fmaxf(m[i], __shfl_xor_sync(0xffffffffu, m[i], 1));
#pragma unroll
    for (int i = 0; i < 4; i++) m[i] = fmaxf(m[i], __shfl_xor_sync(0xffffffffu, m[i], 2));
#pragma unroll
    for (int i = 0; i < 4; i++) { v0[i] = ex2(v0[i] - m[i]); v1[i] = ex2(v1[i] - m[i]); l[i] = v0[i] + v1[i]; }
#pragma unroll
    for (int i = 0; i < 4; i++) l[i] += __shfl_xor_sync(0xffffffffu, l[i], 1);
#pragma unroll
    for (int i = 0; i < 4; i++) l[i] += __shfl_xor_sync(0xffffffffu, l[i], 2);
    uint32_t pp[4];
#pragma unroll
    for (int i = 0; i < 4; i++) {
        float r;
        asm("rcp.approx.ftz.f32 %0, %1;" : "=f"(r) : "f"(l[i]));
        r *= gt[i];
        pp[i] = pack2(v0[i] * r, v1[i] * r);
    }
    const uint32_t mc = (cur0 ? 0xffffu : 0u) | (cur1 ? 0xffff0000u : 0u);
    uint32_t p[2][20];
#pragma unroll
    for (int ks = 0; ks < 5; ks++) {
        const uint32_t mk = ks == w ? ~mc : ks == w + 1 ? mc : 0u;
#pragma unroll
        for (int b = 0; b < 2; b++) { p[b][4 * ks] = pp[2 * b] & mk; p[b][4 * ks + 1] = p[b][4 * ks + 2] = 0u; p[b][4 * ks + 3] = pp[2 * b + 1] & mk; }
    }
    pin(p[0]); pin(p[1]);
    const uint64_t dv = mkdesc(sL + 24576 + 25344 + wg * 6144, 384, 128, 0);
    float o[2][12];
    wg_fence();
#pragma unroll
    for (int b = 0; b < 2; b++) {
        wgmma_pv0(o[b], p[b][0], p[b][1], p[b][2], p[b][3], dv + b * 192);
#pragma unroll
        for (int ks = 1; ks < 5; ks++) wgmma_pv(o[b], p[b][4 * ks], p[b][4 * ks + 1], p[b][4 * ks + 2], p[b][4 * ks + 3], dv + b * 192 + ks * 48);
    }
    wg_commit();
    wg_wait<0>(); pin(o[0]); pin(o[1]);
#pragma unroll
    for (int b = 0; b < 2; b++) {
        uint32_t wv[6];
#pragma unroll
        for (int i = 0; i < 6; i++) wv[i] = pack2(o[b][2 * i], o[b][2 * i + 1]);
        store_o(wv, qb * 32 + wg * 8 + b * 4 + w, h, 0, lane);
    }
    __syncwarp();
    if (elect_one()) mbar_arrive(sb + OFF_BAR + B_LD);
    TR2(7, tid == 64);
}

__device__ __noinline__ void exact_rows(int h, int row16, int lane) {
    const bool aug_lane = ((lane & 3) >= 2) != ((h & 1) != 0);
    const uint8_t* a = g_qkv + (size_t)h * HEAD_BYTES + row16 * 768 + lane * 4;
    const uint8_t* gk = g_qkv + (size_t)(32 + h) * HEAD_BYTES + lane * 4;
    const uint8_t* gv = g_qkv + (size_t)(64 + h) * HEAD_BYTES + lane * 4;
    const uint32_t q0 = ldcg_u32(a), q1 = ldcg_u32(a + 384), q2 = ldcg_u32(a + 128), q3 = ldcg_u32(a + 512);
    const uint32_t q4 = aug_lane ? 0u : ldcg_u32(a + 256), q5 = aug_lane ? 0u : ldcg_u32(a + 640);
    float m0 = -INFINITY, m1 = -INFINITY;
#pragma unroll 4
    for (int kg = 0; kg < 256; kg++) {
        const uint8_t* ka = gk + kg * 384;
        float c[4] = {0.f, 0.f, 0.f, 0.f};
        mma16816(c, q0, q1, q2, q3, ldcg_u32(ka), ldcg_u32(ka + 128));
        mma1688(c, q4, q5, ldcg_u32(ka + 256));
        m0 = fmaxf(m0, fmaxf(c[0], c[1])); m1 = fmaxf(m1, fmaxf(c[2], c[3]));
    }
    m0 = fmaxf(m0, __shfl_xor_sync(0xffffffffu, m0, 1)); m1 = fmaxf(m1, __shfl_xor_sync(0xffffffffu, m1, 1));
    m0 = fmaxf(m0, __shfl_xor_sync(0xffffffffu, m0, 2)); m1 = fmaxf(m1, __shfl_xor_sync(0xffffffffu, m1, 2));
    float oc[3][4];
#pragma unroll
    for (int d = 0; d < 3; d++) oc[d][0] = oc[d][1] = oc[d][2] = oc[d][3] = 0.f;
#pragma unroll 2
    for (int kg = 0; kg < 256; kg += 2) {
        uint32_t kk[2][3], vv[2][3], pp[2][2];
#pragma unroll
        for (int e = 0; e < 2; e++)
#pragma unroll
            for (int d = 0; d < 3; d++) { kk[e][d] = ldcg_u32(gk + (kg + e) * 384 + d * 128); vv[e][d] = ldcg_u32(gv + (kg + e) * 384 + d * 128); }
#pragma unroll
        for (int e = 0; e < 2; e++) {
            float c[4] = {0.f, 0.f, 0.f, 0.f};
            mma16816(c, q0, q1, q2, q3, kk[e][0], kk[e][1]);
            mma1688(c, q4, q5, kk[e][2]);
            pp[e][0] = pack2(ex2(c[0] - m0), ex2(c[1] - m0));
            pp[e][1] = pack2(ex2(c[2] - m1), ex2(c[3] - m1));
        }
#pragma unroll
        for (int d = 0; d < 3; d++) mma16816(oc[d], pp[0][0], pp[0][1], pp[1][0], pp[1][1], movm_t(vv[0][d]), movm_t(vv[1][d]));
    }
    float o[12];
#pragma unroll
    for (int i = 0; i < 12; i++) o[i] = oc[i >> 2][i & 3];
    const int row = row16 * 16 + (lane >> 2);
    float l0, l1;
    uint32_t w[6];
    finish_o(o, w, h & 1, 1.f - ldcg_f32(g_gate + row), 1.f - ldcg_f32(g_gate + row + 8), lane, l0, l1);
    store_o(w, row16, h, 80, lane);
}

__device__ __forceinline__ uint32_t frag_off(int mh, int item) {
    return item < 5 ? 40960 + (mh * 2 + item) * 8192 : (item == 9 && mh) ? OFF_F : mh * 40960 + (item - 5) * 8192;
}
__device__ __forceinline__ void load_frag(uint32_t sb, int bid, int mh, int part) {
    const uint32_t fb = sb + OFF_BAR + B_AF + mh * 32 + part * 8;
    const uint2* src = g_att + (((bid >> 5) * 8 + mh * 4 + ((bid >> 3) & 3)) * 160 + (bid & 1) * 40 + (part ? 64 + part * 16 : 0)) * 128;
    if (part == 0) mbar_expect_tx(fb, 16384);
    bulk_g2s(sb + frag_off(mh, part ? 3 + 2 * part : 0), src, (part == 2 && !mh) ? 24576 : 16384, fb);
    if (part == 2 && mh) bulk_g2s(sb + OFF_F, src + 2048, 8192, fb);
}
__device__ __forceinline__ uint32_t* atta_out(int bid) { return g_flag + (F_ATTA + (bid & 3) * 2 + (bid >> 6)) * 32; }
__device__ __forceinline__ uint32_t* attb_out(int bid, int wg) { return g_flag + (F_ATTB + ((bid & 3) * 4 + wg) * 2 + (bid >> 6)) * 32; }
__device__ __forceinline__ uint32_t* atta_in(int bid) { return g_flag + (F_ATTA + (bid >> 5) * 2 + (bid & 1)) * 32; }
__device__ __forceinline__ uint32_t* attb_in(int bid) { return g_flag + (F_ATTB + (bid >> 3) * 2 + (bid & 1)) * 32; }
#define SVC __forceinline__
__device__ SVC void service(uint32_t sb, int step, uint32_t aflag) {
    const uint32_t bars = sb + OFF_BAR;
    const int bid = fresh_bid(), h = bid >> 2, qb = bid & 3;
    if (step == 0) {
        bulk_wait_all();
        flag_add_done(g_flag + (F_QKVA + P1_NTA(P1_NT(bid))) * 32);
        load_kv(sb, h, 3, 20, 6, 12); load_kv(sb, h, 3, 26, 6, 0);
    } else if (step == 3) {
        mbar_wait(bars + B_RET + 24, 0);
        load_wo(sb, 0, 3); load_wo(sb, 3, 4);
    } else if (step == 4) {
        mbar_wait(bars + B_LD, 0);
        flag_add_done(atta_out(bid));
    } else if (step == 2) {
        if (aflag >= 16) {
            mbar_wait(bars + B_R26, 0);
            asm volatile("fence.acquire.gpu;" ::: "memory");
            load_frag(sb, bid, 0, 0); load_frag(sb, bid, 1, 0);
        }
    } else {
        mbar_wait(bars + B_RET, 0);
        fence_async_smem();
        const int halo = qb ? 768 : 0;
        const uint8_t* src = g_qkv + (size_t)(96 + h) * HEAD_BYTES + qb * 24576;
        mbar_expect_tx(bars + B_L, 3 * 24576 + 2 * halo);
        bulk_g2s(sb + OFF_L, src, 24576, bars + B_L);
        bulk_g2s(sb + OFF_L + 24576 + 768 - halo, src + (size_t)32 * HEAD_BYTES - halo, 24576 + halo, bars + B_L);
        bulk_g2s(sb + OFF_L + 24576 + 25344 + 768 - halo, src + (size_t)64 * HEAD_BYTES - halo, 24576 + halo, bars + B_L);
    }
}

__global__ void __cluster_dims__(2, 1, 1) __launch_bounds__(512, 1)
k_fused(const __grid_constant__ CUtensorMap tmX, const __grid_constant__ CUtensorMap tmWb, const __grid_constant__ CUtensorMap tmWa,
        const __grid_constant__ CUtensorMap tmS, const __nv_bfloat16* __restrict__ x, const __nv_bfloat16* __restrict__ gate_w,
        const uint8_t* __restrict__ wb, const uint8_t* __restrict__ woa, const uint8_t* __restrict__ wob,
        __nv_bfloat16* __restrict__ out) {
    extern __shared__ __align__(1024) uint8_t smem_raw[];
    const uint32_t sb = smem_u32(smem_raw);
    if (sb & 1023u) __trap();
    const uint32_t bars = sb + OFF_BAR;
    float* s_misc = reinterpret_cast<float*>(smem_raw + OFF_BAR + B_MISC);
    const int bid = blockIdx.x;
    const int h = bid >> 2, qb = bid & 3;

    {
        const int warp = __shfl_sync(0xffffffffu, threadIdx.x >> 5, 0), lane = threadIdx.x & 31;
        const int mt = P1_MP(bid) * 2 + (bid & 1), nt = P1_NT(bid);
        TRINIT(); TR(0, threadIdx.x == 0);
        if (warp >= 12 && warp < 12 + PF) {
            if (lane < 15) asm volatile("prefetch.global.L2 [%0];" ::"l"(wb + (warp - 12) * 245760 + bid * 1920 + lane * 128) : "memory");
            if (lane >= 16) asm volatile("prefetch.global.L2 [%0];" ::"l"(x + (size_t)(bid * 16 + lane - 16) * DM + (warp - 12) * 64) : "memory");
        }
        if (threadIdx.x == 352) {
            prefetch_tmap(&tmX);
#pragma unroll
            for (int i = 0; i < 6; i++) mbar_init(bars + B_FULL + 8 * i, 1);
            fence_mbar_init();
        } else if (threadIdx.x == 256) {
            prefetch_tmap(&tmWb);
        } else if (threadIdx.x == 32) {
#pragma unroll
            for (int i = 0; i < 6; i++) mbar_init(bars + B_EMPTY + 8 * i, 16);
#pragma unroll
            for (int i = 0; i < 4; i++) mbar_init(bars + B_PUB + 8 * i, 4);
            fence_mbar_init();
        } else if (threadIdx.x == 64) {
            mbar_init(bars + B_STGB, 8); mbar_init(bars + B_STGA, 8);
            mbar_init(bars + B_RET, 16); mbar_init(bars + B_RET + 8, 8); mbar_init(bars + B_RET + 16, 16); mbar_init(bars + B_RET + 24, 16);
            mbar_init(bars + B_LD, 16); mbar_init(bars + B_NRM, 4); mbar_init(bars + B_HLP, 4);
            fence_mbar_init();
        } else if (threadIdx.x == 128) {
#pragma unroll
            for (int i = 0; i < 10; i++) mbar_init(bars + B_XCH + 8 * i, 1);
            fence_mbar_init();
#pragma unroll
            for (int i = 0; i < 2; i++) {
                mbar_expect_tx(bars + B_XCH + 8 * i, 10240);
                mbar_expect_tx(bars + B_AF + 32 * i + 8, 16384); mbar_expect_tx(bars + B_AF + 32 * i + 16, 24576);
            }
        } else if (threadIdx.x == 160) {
            mbar_init(bars + B_AE, 8); mbar_init(bars + B_R26, 16); mbar_init(bars + B_W0, 8); mbar_init(bars + B_W0 + 8, 8); mbar_init(bars + B_W0 + 16, 8);
            fence_mbar_init();
        } else if (threadIdx.x == 96) {
#pragma unroll
            for (int i = 0; i < 11; i++) mbar_init(bars + B_KV + 8 * i, i == 3 ? 2 : 1);
            s_misc[-4] = 0.f; s_misc[-3] = 0.f;
            fence_mbar_init();
        }
        __syncwarp();
        cluster_arrive();
        if (warp == 11 && elect_one()) {
            tma_x(sb + OFF_X, &tmX, 0, mt * 8, bars + B_FULL);
#pragma unroll
            for (int i = 0; i < 6; i++) mbar_expect_tx(bars + B_FULL + 8 * i, (i & 1) ? 16384 : 32768);
        }
        __syncwarp();
        cluster_wait();
        const uint32_t t_start = clock_lo();
        if ((warp == 8 || warp == 10) && elect_one()) {
            const int col = (bid & 1) * 128 + (warp == 10 ? 64 : 0);
#pragma unroll
            for (int i = 0; i < 2; i++) tma_3d_mc(sb + i * 16384 + col * 64, &tmWb, col, nt, i * 32, bars + B_FULL + 8 * i, 3);
        }
        __syncwarp();

        if (warp < 8) {
            asm volatile("setmaxnreg.inc.sync.aligned.u32 152;");
            const int wg = warp >> 2, t = lane & 3;
            float acc0[64], acc1[56];
#pragma unroll
            for (int i = 0; i < 64; i++) acc0[i] = 0.f;
#pragma unroll
            for (int i = 0; i < 56; i++) acc1[i] = 0.f;
            pin(acc0); pin(acc1);
            const uint64_t da0 = mkdesc(sb + OFF_X + wg * 8192, 16, 1024, 1), db0 = mkdesc(sb, 4096, 1024, 1);
            uint32_t rel;
            asm volatile("mapa.shared::cluster.u32 %0, %1, %2;" : "=r"(rel) : "r"(bars + B_EMPTY), "r"(lane & 1));
            uint32_t xs = 0, xprev = 0, ph = 0;
#pragma unroll 1
            for (int br = 0; br < 2; br++) {
#pragma unroll 1
                for (int kp = 0; kp < 10; kp++) {
                    const uint64_t da = da0 + xs * 1024, db = db0 + xs * 2048;
#pragma unroll
                    for (int e = 0; e < 2; e++) {
                        mbar_wait(bars + B_FULL + 16 * xs + 8 * e, ph);
                        TR(1 + 3 * br, threadIdx.x == 0 && kp + e == 0);
                        wg_fence();
                        wgmma_ss128(acc0, da + e * 4, db + e * 1024, e ? 1 : kp);
                        wgmma_ss112(acc1, da + e * 4, db + e * 1024 + 512, e ? 1 : kp);
                        wgmma_ss128(acc0, da + e * 4 + 2, db + e * 1024 + 128, 1);
                        wgmma_ss112(acc1, da + e * 4 + 2, db + e * 1024 + 640, 1);
                        wg_commit();
                        wg_wait<1>();
                        if (lane < 2 && kp + e > 0) asm volatile("mbarrier.arrive.shared::cluster.b64 _, [%0];" ::"r"(e ? rel + 16 * xs : rel + 16 * xprev + 8) : "memory");
                    }
                    xprev = xs;
                    if (++xs == 3) { xs = 0; ph ^= 1; }
                }
                wg_wait<0>();
                pin(acc0); pin(acc1);
                if (lane < 2) asm volatile("mbarrier.arrive.shared::cluster.b64 _, [%0];" ::"r"(rel + 16 * xprev + 8) : "memory");
                TR(2 + 3 * br, threadIdx.x == 0);
                if (br == 1) named_sync(1, 256);
                else mbar_wait(bars + B_HDR, 0);
                const uint32_t wst = sb + (br == 0 ? OFF_R : 0) + warp * 768 + (lane & 7) * 16;
                const uint32_t a0 = wst + (lane >> 3) * 128;
                const uint32_t a1 = wst + (lane < 16 ? 512 + (lane >> 3) * 128 : 6144 + ((lane >> 3) - 2) * 128);
                const uint32_t a2 = wst + 6144 + 256 + (lane >> 3) * 128;
                const bool poly = (POLY16 >> ((mt * 8 + warp) & 15)) & 1;
                const uint32_t augq = br ? 0u : (t & 1) ? 0x00003D2Du : 0x3F8043C0u;
                const uint32_t augk = br ? 0u : (t & 1) ? (poly ? 0u : 0x00003F80u) : (poly ? 0x00003F80u : 0x3F800000u);
                const uint32_t augv = (t & 1) ? 0u : 0x00003F80u;
                const float sc2 = br ? 0.5f * QSCALE : QSCALE;
                const int hp0 = (br ? P1_NTA(nt) : nt) * 6;
#pragma unroll
                for (int u = 0; u < 6; u++) {
                    uint32_t v[2][5];
#define ACC(i) ((i) < 64 ? acc0[(i) & 63] : acc1[((i) - 64) % 56])
                    if (hp0 + u < 16) {
#pragma unroll
                        for (int j = 0; j < 10; j++) {
                            const int i = (5 * u + j % 5) * 4 + 2 * (j / 5);
                            const float f = j % 5 == 2 ? sc2 : QSCALE;
                            v[j / 5][j % 5] = pack2(ACC(i) * f, ACC(i + 1) * f);
                        }
                    } else {
#pragma unroll
                        for (int j = 0; j < 10; j++) { const int i = (5 * u + j % 5) * 4 + 2 * (j / 5); v[j / 5][j % 5] = pack2(ACC(i), ACC(i + 1)); }
                    }
#undef ACC
                    const uint32_t aug = hp0 + u < 16 ? augq : hp0 + u < 32 ? augk : augv;
                    stsm4(a0 + u * 12288, v[0][0], v[0][1], t < 2 ? v[0][2] : aug, v[1][0]);
                    stsm4(a1 + u * 12288, v[1][1], t < 2 ? v[1][2] : aug, v[0][3], v[0][4]);
                    stsm4(a2 + u * 12288, t < 2 ? aug : v[0][2], v[1][3], v[1][4], t < 2 ? aug : v[1][2]);
                }
                fence_async_smem();
                __syncwarp();
                if (lane == 0) mbar_arrive(bars + B_STGB + 8 * br);
                TR(3 + 3 * br, threadIdx.x == 0);
            }
            asm volatile("setmaxnreg.dec.sync.aligned.u32 128;");
        } else if (warp < 12) {
            asm volatile("setmaxnreg.dec.sync.aligned.u32 80;");
            if (warp != 9) {
                if (warp == 11) {
                    uint32_t xs = 0, ph = 0;
#pragma unroll
                    for (int i = 1; i < 3; i++) {
                        while (clock_lo() - t_start < (i == 1 ? G1 : G2)) {}
                        if (elect_one()) tma_x(sb + OFF_X + i * 16384, &tmX, i * 64, mt * 8, bars + B_FULL + 16 * i);
                    }
#pragma unroll 1
                    for (int P = 3; P < 20; P++) {
                        const int k0 = (P < 10 ? P : P - 13) * 64;
                        mbar_wait(bars + B_EMPTY + 16 * xs + 8, ph);
                        if (elect_one()) {
                            if (k0 >= 0) tma_x(sb + OFF_X + xs * 16384, &tmX, k0, mt * 8, bars + B_FULL + 16 * xs);
                            if (P == 7) { prefetch_tmap(&tmWa); prefetch_tmap(&tmS); }
                        }
                        if (++xs == 3) { xs = 0; ph ^= 1; }
                    }
                } else {
                    const int col = (bid & 1) * 128 + (warp == 10 ? 64 : 0);
                    uint32_t s = 0, ph = 0;
#pragma unroll
                    for (int i = 2; i < 6; i++) {
                        while (clock_lo() - t_start < (i < 4 ? G1 : G2)) {}
                        if (elect_one()) tma_3d_mc(sb + i * 16384 + col * 64, &tmWb, col, nt, i * 32, bars + B_FULL + 8 * i, 3);
                    }
#pragma unroll 1
                    for (int it = 6; it < 40; it++) {
                        const int k0 = (it < 20 ? it : it < 26 ? it - 6 : it - 26) * 32;
                        const CUtensorMap* tw = it >= 20 ? &tmWa : &tmWb;
                        const int ct = it >= 20 ? P1_NTA(nt) : nt;
                        const int bytes = ((s & 1) || (it >= 20 && it < 26)) ? 16384 : 32768;
                        mbar_wait(bars + B_EMPTY + 8 * s, ph);
                        if (elect_one()) {
                            tma_3d_mc(sb + s * 16384 + col * 64, tw, col, ct, k0, bars + B_FULL + 8 * s, 3);
                            if (warp == 8) mbar_expect_tx(bars + B_FULL + 8 * s, bytes);
                        }
                        if (++s == 6) { s = 0; ph ^= 1; }
                    }
                }
                if (warp == 8 && elect_one()) {
                    mbar_wait(bars + B_KV, 0);
                    load_kv(sb, h, 1, 4, 4, 6);
                    bulk_g2s(sb + OFF_R + 12288, g_qkv + (size_t)h * HEAD_BYTES + qb * 24576 + 12288, 12288, bars + B_KV + 8);
                    mbar_wait(bars + B_EMPTY + 24, 0);
                    load_kv(sb, h, 2, 8, 1, 12); load_kv(sb, h, 2, 9, 11, 0);
                }
            } else {
                if (elect_one()) {
                    mbar_wait(bars + B_HLP, 0);
                    bulk_s2g(g_wo + bid * 800, sb + OFF_R, 12800);
                    bulk_s2g(g_gate + bid * 16, sb + OFF_R + 12800, 64);
                    bulk_commit();
                    bulk_wait_all();
                    mbar_arrive(bars + B_HDR);
                    flag_add_done(g_flag + F_HELP * 32);
                    TR2(53, true);
                    mbar_wait(bars + B_STGB, 0);
                    uint32_t tick = clock_lo();
#pragma unroll 1
                    for (int i = 0; i < 24; i++) {
                        while (clock_lo() - tick < PACE) {}
                        tick += PACE;
                        bulk_s2g(g_qkv + (size_t)(nt * 12 + (i >> 1)) * HEAD_BYTES + mt * 6144 + (i & 1) * 3072, sb + OFF_R + i * 3072, 3072);
                    }
                    mbar_wait(bars + B_NRM, 0);
                    bulk_s2g(g_nrm + mt * 96 + nt * 12, bars + B_MISC, 48);
                    bulk_commit();
                    bulk_wait_all();
                    flag_add_done(g_flag + (F_QKVB + nt) * 32);
                    TR(8, true);
                    flag_wait_head(g_flag + F_QKVB * 32, h, 128);
                    fence_async_smem();
                    TR(9, true);
                    load_kv(sb, h, 0, 0, 4, 6);
                    bulk_g2s(sb + OFF_R, g_qkv + (size_t)h * HEAD_BYTES + qb * 24576, 12288, bars + B_KV);
                }
                __syncwarp();
                {
                    const uint32_t w = ldcg_u32(g_nrm + (lane < 16 ? lane * 96 + 32 + h : (qb * 4 + (lane & 3)) * 96 + h));
                    const float kn = __uint_as_float(__reduce_max_sync(0xffffffffu, lane < 16 ? w : 0u));
                    if (lane >= 16 && lane < 20) s_misc[lane] = __uint_as_float(w) * kn <= SCORE_LIMIT2 ? 0.f : 1.f;
                    __syncwarp();
                    if (elect_one()) mbar_arrive(bars + B_KV + 24);
                }
            }
            __syncwarp();
            named_sync(5, 128);
            asm volatile("setmaxnreg.inc.sync.aligned.u32 128;");
        } else {
            mbar_wait(bars + B_FULL + 40, 0);
            {
                uint4 wv[7];
#pragma unroll
                for (int e = 0; e < 7; e++) {
                    const int i = threadIdx.x - 384 + e * 128, d = bid * 800 + i;
                    const int kr = d & 7, ng = (d >> 3) % 20, kg = (d / 160) % 80, part = bid >> 4;
                    const int k = (kg < 40 ? kg : kg + 40) * 8 + (part & 1) * 320 + kr;
                    const uint8_t* src = (k < 640 ? woa + k * 1280 : wob + (k - 640) * 1280) + ((part >> 1) * 20 + ng) * 16;
                    if (i < 800) wv[e] = __ldg(reinterpret_cast<const uint4*>(src));
                }
                const uint2* gw = reinterpret_cast<const uint2*>(gate_w) + lane;
                const uint2* xr = reinterpret_cast<const uint2*>(x + (size_t)(bid * 16 + (warp - 12) * 4) * DM) + lane;
                uint2 gv[5], xv[4][5];
#pragma unroll
                for (int i = 0; i < 5; i++) gv[i] = __ldg(gw + 32 * i);
#pragma unroll
                for (int i = 0; i < 20; i++) xv[i / 5][i % 5] = __ldg(xr + 32 * i);
                float a[4];
#pragma unroll
                for (int e = 0; e < 4; e++) {
                    a[e] = 0.f;
#pragma unroll
                    for (int i = 0; i < 5; i++) {
                        a[e] = fmaf(bf_lo(xv[e][i].x), bf_lo(gv[i].x), a[e]); a[e] = fmaf(bf_hi(xv[e][i].x), bf_hi(gv[i].x), a[e]);
                        a[e] = fmaf(bf_lo(xv[e][i].y), bf_lo(gv[i].y), a[e]); a[e] = fmaf(bf_hi(xv[e][i].y), bf_hi(gv[i].y), a[e]);
                    }
                }
#pragma unroll
                for (int o = 16; o; o >>= 1) {
#pragma unroll
                    for (int e = 0; e < 4; e++) a[e] += __shfl_xor_sync(0xffffffffu, a[e], o);
                }
                const float z = lane == 0 ? a[0] : lane == 1 ? a[1] : lane == 2 ? a[2] : a[3];
                if (lane < 4) asm volatile("st.shared.f32 [%0], %1;" ::"r"(sb + OFF_R + 12800 + ((lane & 1) * 8 + (warp - 12) * 2 + (lane >> 1)) * 4), "f"(__fdividef(1.f, 1.f + __expf(-z))) : "memory");
#pragma unroll
                for (int e = 0; e < 7; e++) {
                    const int i = threadIdx.x - 384 + e * 128;
                    if (i < 800) asm volatile("st.shared.v4.b32 [%0], {%1,%2,%3,%4};" ::"r"(sb + OFF_R + i * 16), "r"(wv[e].x), "r"(wv[e].y), "r"(wv[e].z), "r"(wv[e].w) : "memory");
                }
                fence_async_smem();
                __syncwarp();
                if (lane == 0) mbar_arrive(bars + B_HLP);
            }
            mbar_wait(bars + B_STGB, 0);
#pragma unroll 1
            for (int hs = warp - 12; hs < 12; hs += 4) {
                uint32_t nm = 0;
                if (nt * 12 + hs < 64) {
#pragma unroll
                    for (int i = 0; i < 4; i++) {
                        const uint32_t a = sb + OFF_R + hs * 6144 + (i * 4 + (lane >> 3)) * 384 + (lane & 7) * 16;
                        const uint4 k0 = lds128(a), k1 = lds128(a + 128);
                        uint32_t k2, k3;
                        asm volatile("ld.shared.v2.b32 {%0,%1}, [%2];" : "=r"(k2), "=r"(k3) : "r"(a + 256 + (hs & 1) * 8));
                        uint32_t n0 = hfma2(k2, k2, 0u), n1 = hfma2(k3, k3, 0u);
                        n0 = hfma2(k0.x, k0.x, n0); n1 = hfma2(k0.y, k0.y, n1); n0 = hfma2(k0.z, k0.z, n0); n1 = hfma2(k0.w, k0.w, n1);
                        n0 = hfma2(k1.x, k1.x, n0); n1 = hfma2(k1.y, k1.y, n1); n0 = hfma2(k1.z, k1.z, n0); n1 = hfma2(k1.w, k1.w, n1);
                        nm = max(nm, __float_as_uint((bf_lo(n0) + bf_hi(n0)) + (bf_lo(n1) + bf_hi(n1))));
                    }
                }
                nm = __reduce_max_sync(0xffffffffu, nm);
                if (lane == 0) s_misc[hs] = __uint_as_float(nm) * 1.03f;
            }
            fence_async_smem();
            __syncwarp();
            if (lane == 0) mbar_arrive(bars + B_NRM);
        }
    }

    uint32_t aflag;
    {
        const uint64_t dK0 = mkdesc(sb, 128, 384, 0), dK1 = mkdesc(sb + 256, 0, 384, 0), dV = mkdesc(sb, 384, 128, 0);
        const int wid = fresh_wid();
        mbar_wait(bars + B_KV, 0);
        TR(10 + (threadIdx.x >> 7), (threadIdx.x & 127) == 0);
#pragma unroll 1
        for (int u = 0; u < 2; u++) {
            uint32_t q[8];
            {
                const uint32_t a = sb + OFF_R + (u * 32 + here(wid) * 2) * 384 + (fresh_tid() & 31) * 4;
                q[0] = lds32(a); q[1] = lds32(a + 384); q[2] = lds32(a + 128); q[3] = lds32(a + 512);
                q[4] = lds32(a + 256); q[5] = lds32(a + 640);
                q[6] = lds32(bars + B_ZERO); q[7] = lds32(bars + B_ZERO + 4);
            }
            float o[12];
#pragma unroll
            for (int i = 0; i < 12; i++) o[i] = 0.f;
            pin(o); pin(q);
            float s0[32], s1[32];
            uint32_t p[16];
            float g0, g1;

            wg_fence(); qk_tile(s0, q, dK0 + (k_off(0) >> 4), dK1 + (k_off(0) >> 4)); wg_commit();
#pragma unroll
            for (int j = 0; j < 32; j += 2) {
                FENCE2(); qk_tile(s1, q, dK0 + (k_off(j + 1) >> 4), dK1 + (k_off(j + 1) >> 4)); wg_commit();
                wg_wait<1>(); pin(s0);
                exp_tile(s0, p, POLY16 >> (4 * (j & 3)));
                pin(p);
                wg_fence(); pv_tile(o, p, dV + (v_off(j) >> 4), POLY16 >> (4 * (j & 3))); wg_commit();
                if (j == 2 || j == 6 || j == 18) { mbar_wait(bars + B_KV + (j == 2 ? 8 : j == 6 ? 16 : 24), 0); wg_fence(); }
                const bool ahead = j + 2 < 32 && j != LJ;
                if (ahead) { FENCE2(); qk_tile(s0, q, dK0 + (k_off(j + 2) >> 4), dK1 + (k_off(j + 2) >> 4)); wg_commit(); }
                {
                    TR(32 + u * 4 + j / 8, (j & 7) == 0 && fresh_tid() == 128);
                    if (j == 10) { if (u == 1 && elect_one()) mbar_arrive(bars + B_RET); }
                    if (j == SAJ) {
                        if (u == 0 && wid == 14 && elect_one()) {
                            const int bid = fresh_bid();
                            mbar_wait(bars + B_STGA, 0);
                            tma_store_3d(&tmS, sb, 0, (P1_MP(bid) * 2 + (bid & 1)) * 16, 96 + P1_NTA(P1_NT(bid)) * 12);
                            bulk_commit();
                        }
                        __syncwarp();
                    }
                    if (j == 12) {
                        if (u == 0 && wid == 14 && elect_one()) service(sb, 0, 0);
                        __syncwarp();
                    }
                    if (j == S1J) { if (u == 1 && wid == S1T && elect_one()) service(sb, 1, 0); __syncwarp(); }
                    if (j == 20 || j == 26) { if (u == 1 && elect_one()) mbar_arrive(bars + (j == 20 ? B_RET + 24 : B_R26)); }
                    if (j == S4J) { if (u == 1 && wid == S4T && elect_one()) service(sb, 4, 0); __syncwarp(); }
                    if (j == S3J) { if (u == 1 && wid == S3T && elect_one()) service(sb, 3, 0); __syncwarp(); }
                    if (j == 28) { if (u == 1 && wid == 10 && elect_one()) service(sb, 2, aflag); __syncwarp(); }
                    if (j == 26) {
                        const float* gp = g_gate + (fresh_bid() & 3) * 512 + u * 256 + here(wid) * 16 + ((fresh_tid() & 31) >> 2);
                        g0 = ldcg_f32(gp); g1 = ldcg_f32(gp + 8);
                        aflag = ld_relaxed(atta_in(fresh_bid()));
                    }
                }
                if (ahead) wg_wait<1>(); else wg_wait<0>();
                pin(s1);
                exp_tile(s1, p, POLY16 >> (4 * ((j + 1) & 3)));
                pin(p);
                wg_fence(); pv_tile(o, p, dV + (v_off(j + 1) >> 4), POLY16 >> (4 * ((j + 1) & 3))); wg_commit();
                if (j == LJ) {
                    TR2(27, j == LJ && u == 1 && fresh_tid() == 64);
                    wg_wait<0>();
                    if (u == 1) local_attn(sb, here(wid));
                    wg_fence(); qk_tile(s0, q, dK0 + (k_off(j + 2) >> 4), dK1 + (k_off(j + 2) >> 4)); wg_commit();
                }
            }
            const int tid = fresh_tid(), lane = tid & 31, warp = here(wid);
            const int bid = fresh_bid(), h = bid >> 2, qb = bid & 3;
            if (u == 0 && wid == 13 && elect_one())
                flag_wait_head(g_flag + F_QKVA * 32, h, 0);
            __syncwarp();
            wg_wait<0>(); pin(o);
            TR(14 + u * 4 + (tid >> 7), (tid & 127) == 0);
            if (u == 1 && lane == 0) mbar_arrive(bars + B_RET + 16);
            float l0, l1;
            uint32_t w[6];
            finish_o(o, w, h & 1, 1.f - g0, 1.f - g1, lane, l0, l1);
            store_o(w, qb * 32 + u * 16 + warp, h, 80, lane);
            const float sum = (((o[0] + o[1]) + (o[2] + o[3])) + ((o[4] + o[5]) + (o[6] + o[7]))) + ((o[8] + o[9]) + (o[10] + o[11]));
            if (__any_sync(0xffffffffu, !(l0 >= 9.3132257e-10f && l1 >= 9.3132257e-10f && fabsf(sum) <= 1e37f && s_misc[16 + u * 2 + (warp >> 3)] == 0.f)))
                exact_rows(h, qb * 32 + u * 16 + warp, lane);
        }
        __syncwarp();
        if (elect_one()) mbar_arrive(bars + B_PUB + (wid >> 2) * 8);
    }

    {
        const int tid = fresh_tid(), lane = tid & 31;
        const int warp = __shfl_sync(0xffffffffu, tid >> 5, 0);
        const int bid = fresh_bid(), rank = bid & 1;
        if (warp >= 8) {
            asm volatile("setmaxnreg.dec.sync.aligned.u32 40;");
            if ((warp == 8 || warp == 9 || warp == 12 || warp == 14) && elect_one()) {
                const int wg = warp == 9 ? 0 : warp == 14 ? 1 : warp >> 2;
                mbar_wait(bars + B_PUB + 8 * wg, 0);
                TR2(48 + wg, true);
                flag_add_done(attb_out(bid, wg));
                TR2(wg == 0 ? 54 : wg == 1 ? 55 : wg == 2 ? 61 : 62, true);
            }
            if (warp == 13 && elect_one()) {
#pragma unroll
                for (int i = 0; i < 3; i++) { mbar_wait(bars + B_W0 + 8 * (i ? i : 1), 0); load_wo(sb, 7 + i, 1); }
                TR2(57, true);
            }
            if (warp == 10 && elect_one()) {
                if (aflag < 16) flag_wait(atta_in(bid), 16);
                mbar_wait(bars + B_RET + 16, 0);
                if (aflag < 16) { load_frag(sb, bid, 0, 0); load_frag(sb, bid, 1, 0); }
                mbar_wait(bars + B_W0, 0);
                load_frag(sb, bid, 0, 1);
                mbar_wait(bars + B_W0 + 8, 0);
                load_frag(sb, bid, 0, 2);
                TR2(56, true);
            }
            if (warp == 11 && elect_one()) {
                mbar_wait(bars + B_AE, 0);
                fence_async_smem();
                flag_wait_fast(attb_in(bid), 16);
                TR2(52, true);
                load_frag(sb, bid, 1, 1); load_frag(sb, bid, 1, 2);
                if (atomicAdd(g_flag + F_EXIT * 32, 1u) == 127u) {
#pragma unroll 1
                    for (int i = 0; i < F_COUNT; i++) g_flag[i * 32] = 0u;
                }
            }
        } else {
            const int mh = warp >> 2;
            const int mt64 = (bid >> 5) * 8 + mh * 4 + ((bid >> 3) & 3);
            const int pos = frag_pos(warp & 3, lane);
            const uint2* ap = g_att + (mt64 * 160 + rank * 40) * 128 + pos;
            const uint32_t as0 = sb + frag_off(mh, 0) + pos * 8, as1 = sb + frag_off(mh, 5) + pos * 8, as9 = sb + frag_off(mh, 9) + pos * 8, fb = bars + B_AF + mh * 32;
            const uint64_t db = mkdesc(sb, 2560, 128, 0);
            TR(22, tid == 0);
            uint32_t a[6][16];
            auto ldg = [&](int i) {
#pragma unroll
                for (int j = 0; j < 8; j++)
                    asm volatile("ld.global.L1::no_allocate.v2.b32 {%0, %1}, [%2];" : "=r"(a[i % 6][2 * j]), "=r"(a[i % 6][2 * j + 1])
                                 : "l"(ap + ((i / 5) * 80 + (i % 5) * 8 + j) * 128) : "memory");
            };
            auto lds = [&](int i) {
                if (i == 0 || i == 5 || i == 7) mbar_wait(fb + (i / 3) * 8, 0);
#pragma unroll
                for (int j = 0; j < 8; j++)
                    asm volatile("ld.shared.v2.b32 {%0, %1}, [%2];" : "=r"(a[i % 6][2 * j]), "=r"(a[i % 6][2 * j + 1])
                                 : "r"(i == 9 ? as9 + j * 1024 : (i < 5 ? as0 : as1) + ((i % 5) * 8 + j) * 1024) : "memory");
            };
            asm volatile("setmaxnreg.inc.sync.aligned.u32 216;");
            float snd[40], keep[40];
            const uint64_t dk = db + rank * 80, ds = db + (rank ^ 1) * 80;
            TR(23, tid == 0);
            auto half = [&](float (&acc)[40], uint64_t d, int i) {
#pragma unroll
                for (int k = 0; k < 4; k++)
                    if (i + k == 0) wgmma_rs80f(acc, a[0][0], a[0][1], a[0][2], a[0][3], d + (wo_off(0) >> 4));
                    else wgmma_rs80(acc, a[i % 6][4 * k], a[i % 6][4 * k + 1], a[i % 6][4 * k + 2], a[i % 6][4 * k + 3], d + (wo_off(i) >> 4) + k * 320);
            };
            auto mma = [&](int i) {
                if (i == 0 || wo_bar(i) != wo_bar(i - 1)) mbar_wait(bars + B_WO + 8 * wo_bar(i), 0);
                pin(a[i % 6]);
                TR2(24, tid == 0 && i == 0);
                wg_fence();
                half(snd, ds, i);
                if (i < 10 - DEFER) half(keep, dk, i);
                wg_commit();
            };
            lds(0); lds(1);
            mma(0);
            ldg(2); ldg(3);
            mma(1);
            if (lane == 0) mbar_arrive(bars + B_AE);
            ldg(4);
#pragma unroll
            for (int i = 0; i < 3; i++) {
                wg_wait<1>();
                if (lane == 0) mbar_arrive(bars + B_W0 + 8 * i);
                mma(i + 2);
            }
            wg_wait<0>();
            if (lane == 0) mbar_arrive_cluster(bars + B_RET + 8, rank ^ 1);
            lds(5); mma(5);
            lds(6); mma(6);
            lds(7); mma(7);
            lds(8); mma(8);
            lds(9); mma(9);
#pragma unroll
            for (int i = 10 - DEFER; i < 10; i++) half(keep, dk, i);
            wg_commit();
            const uint32_t xs = sb + (mh ? wo_off(4) : wo_off(3)) + (tid & 127) * 16;
            {
                uint32_t ra, rb;
                asm volatile("mapa.shared::cluster.u32 %0, %1, %2;" : "=r"(ra) : "r"(xs), "r"(rank ^ 1));
                asm volatile("mapa.shared::cluster.u32 %0, %1, %2;" : "=r"(rb) : "r"(bars + B_XCH + 8 * mh), "r"(rank ^ 1));
                mbar_wait(bars + B_RET + 8, 0);
                wg_wait<1>();
                pin(snd);
                TR2(63, tid == 192);
#pragma unroll
                for (int j = 0; j < 5; j++)
                    asm volatile("st.async.weak.shared::cluster.mbarrier::complete_tx::bytes.v4.b32 [%0], {%1,%2,%3,%4}, [%5];"
                                 ::"r"(ra + j * 2048), "r"(pack2(snd[8 * j], snd[8 * j + 1])), "r"(pack2(snd[8 * j + 2], snd[8 * j + 3])),
                                   "r"(pack2(snd[8 * j + 4], snd[8 * j + 5])), "r"(pack2(snd[8 * j + 6], snd[8 * j + 7])), "r"(rb) : "memory");
            }
            named_sync(8 + mh, 128);
            mbar_wait(bars + B_XCH + 8 * mh, 0);
            TR2(58, tid == 192);
            uint4 rcv[10];
#pragma unroll
            for (int j = 0; j < 5; j++) {
                const uint4 v = lds128(xs + j * 2048);
                rcv[2 * j] = make_uint4(v.x << 16, v.x & 0xffff0000u, v.y << 16, v.y & 0xffff0000u);
                rcv[2 * j + 1] = make_uint4(v.z << 16, v.z & 0xffff0000u, v.w << 16, v.w & 0xffff0000u);
            }
            wg_wait<0>();
            pin(keep);
            TR2(25, tid == 0); TR2(60, tid == 192);
            uint32_t w[20];
#pragma unroll
            for (int j = 0; j < 10; j++) {
                const uint4 o = rcv[j];
                w[2 * j] = pack2(keep[4 * j] + __uint_as_float(o.x), keep[4 * j + 1] + __uint_as_float(o.y));
                w[2 * j + 1] = pack2(keep[4 * j + 2] + __uint_as_float(o.z), keep[4 * j + 3] + __uint_as_float(o.w));
            }
            const uint32_t ot = sb + frag_off(mh, 5) + (warp & 3) * 2816;
            const uint32_t sa = ot + (lane & 15) * 176 + (lane >> 4) * 16;
#pragma unroll
            for (int j = 0; j < 5; j++) stsm4(sa + j * 32, w[4 * j], w[4 * j + 1], w[4 * j + 2], w[4 * j + 3]);
            __syncwarp();
            __nv_bfloat16* ob = out + (size_t)(mt64 * 64 + (warp & 3) * 16) * DM + (bid & 7) * 80;
#pragma unroll
            for (int i = 0; i < 5; i++) {
                const int c = lane + 32 * i, r = c / 10;
                stg128(ob + ((r & 7) * 2 + (r >> 3)) * DM + (c % 10) * 8, lds128(ot + r * 176 + (c % 10) * 16));
            }
            TR2(26, tid == 0); TR2(59, tid == 192);
            TRFLUSH();
        }
    }
}

typedef CUresult (*EncodeFn)(CUtensorMap*, CUtensorMapDataType, cuuint32_t, void*, const cuuint64_t*, const cuuint64_t*,
                             const cuuint32_t*, const cuuint32_t*, CUtensorMapInterleave, CUtensorMapSwizzle,
                             CUtensorMapL2promotion, CUtensorMapFloatOOBfill);

void make_map(EncodeFn fn, CUtensorMap* tm, const void* ptr, int rank, const cuuint64_t* dims, const cuuint64_t* strides,
              const cuuint32_t* box, CUtensorMapSwizzle swz) {
    const cuuint32_t es[4] = {1, 1, 1, 1};
    fn(tm, CU_TENSOR_MAP_DATA_TYPE_BFLOAT16, rank, const_cast<void*>(ptr), dims, strides, box, es, CU_TENSOR_MAP_INTERLEAVE_NONE,
       swz, PROMO, CU_TENSOR_MAP_FLOAT_OOB_FILL_NONE);
}

}

extern "C" void kernel_launch(void* const* d_in, const int* in_sizes, int n_in, void* d_out, int out_size) {
    (void)in_sizes; (void)n_in; (void)out_size;
    const __nv_bfloat16* x = (const __nv_bfloat16*)d_in[0];
    const __nv_bfloat16* wqkv_a = (const __nv_bfloat16*)d_in[1];
    const __nv_bfloat16* wo_a = (const __nv_bfloat16*)d_in[2];
    const __nv_bfloat16* wqkv_b = (const __nv_bfloat16*)d_in[4];
    const __nv_bfloat16* wo_b = (const __nv_bfloat16*)d_in[5];
    const __nv_bfloat16* gate_w = (const __nv_bfloat16*)d_in[6];

    void* fnp = nullptr;
    cudaDriverEntryPointQueryResult qr;
    cudaGetDriverEntryPoint("cuTensorMapEncodeTiled", &fnp, cudaEnableDefault, &qr);
    EncodeFn enc = (EncodeFn)fnp;
    void* qkv = nullptr;
    cudaGetSymbolAddress(&qkv, g_qkv);

    CUtensorMap tmX, tmWb, tmWa, tmS;
    {
        const cuuint64_t d[4] = {640, 8, 2, 128}, s[3] = {2560, 1280, 20480};
        const cuuint32_t b[4] = {64, 8, 2, 8};
        make_map(enc, &tmX, x, 4, d, s, b, CU_TENSOR_MAP_SWIZZLE_128B);
    }
    {
        const cuuint64_t d[3] = {240, 8, 640}, s[2] = {480, 3840};
        const cuuint32_t b[3] = {64, 1, 32};
        make_map(enc, &tmWb, wqkv_b, 3, d, s, b, CU_TENSOR_MAP_SWIZZLE_128B);
        make_map(enc, &tmWa, wqkv_a, 3, d, s, b, CU_TENSOR_MAP_SWIZZLE_128B);
    }
    {
        const cuuint64_t d[3] = {192, 256, 192}, s[2] = {384, (cuuint64_t)HEAD_BYTES};
        const cuuint32_t b[3] = {192, 16, 12};
        make_map(enc, &tmS, qkv, 3, d, s, b, CU_TENSOR_MAP_SWIZZLE_NONE);
    }
    cudaFuncSetAttribute(k_fused, cudaFuncAttributeMaxDynamicSharedMemorySize, SMEM_BYTES);
    k_fused<<<128, 512, SMEM_BYTES, cudaStreamPerThread>>>(tmX, tmWb, tmWa, tmS, x, gate_w, (const uint8_t*)wqkv_b,
                                                          (const uint8_t*)wo_a, (const uint8_t*)wo_b, (__nv_bfloat16*)d_out);
}
```

```cpp
#include <cuda_runtime.h>
#include <cuda_bf16.h>
#include <cuda.h>
#include <stdint.h>

namespace {

constexpr int SEQ = 2048, DM = 640;
constexpr int HEAD_BYTES = 256 * 384;
constexpr uint32_t POLY16 = 0xddddu;
constexpr float QSCALE = 0.22360679774997896f * 1.4426950408889634f;

__device__ __align__(1024) uint8_t g_qkv[2 * 96 * HEAD_BYTES];
__device__ __align__(128) float g_gate[SEQ];
__device__ __align__(128) float g_nrm[16 * 96];
enum { F_QKVB = 0, F_QKVA = 8, F_HELP = 16, F_EXIT = 17, F_ATTA = 18, F_ATTB = 26, F_COUNT = 58 };
__device__ uint32_t g_flag[F_COUNT * 32];
__device__ __align__(1024) uint4 g_wo[8 * 160 * 10 * 8];
__device__ __align__(1024) uint2 g_att[32 * 160 * 128];

__device__ __forceinline__ uint32_t smem_u32(const void* p) { return (uint32_t)__cvta_generic_to_shared(p); }
__device__ __forceinline__ void mbar_init(uint32_t bar, int cnt) { asm volatile("mbarrier.init.shared::cta.b64 [%0], %1;" ::"r"(bar), "r"(cnt) : "memory"); }
__device__ __forceinline__ void mbar_expect_tx(uint32_t bar, int bytes) { asm volatile("mbarrier.arrive.expect_tx.shared::cta.b64 _, [%0], %1;" ::"r"(bar), "r"(bytes) : "memory"); }
__device__ __forceinline__ void mbar_arrive(uint32_t bar) { asm volatile("mbarrier.arrive.shared::cta.b64 _, [%0];" ::"r"(bar) : "memory"); }
__device__ __forceinline__ bool mbar_try(uint32_t bar, uint32_t parity) {
    uint32_t ok;
    asm volatile("{\n.reg .pred p;\nmbarrier.try_wait.parity.shared::cta.b64 p, [%1], %2;\nselp.u32 %0, 1, 0, p;\n}\n" : "=r"(ok) : "r"(bar), "r"(parity) : "memory");
    return ok;
}
__device__ __forceinline__ void mbar_wait(uint32_t bar, uint32_t parity) {
    if (mbar_try(bar, parity)) return;
#pragma unroll 1
    for (int i = 0; i < (1 << 21); i++)
        if (mbar_try(bar, parity)) return;
    __trap();
}
__device__ __forceinline__ void fence_mbar_init() { asm volatile("fence.mbarrier_init.release.cluster;" ::: "memory"); }
__device__ __forceinline__ void tma_x(uint32_t dst, const CUtensorMap* tm, int k, int blk16, uint32_t bar) {
    asm volatile("cp.async.bulk.tensor.4d.shared::cluster.global.mbarrier::complete_tx::bytes [%0], [%1, {%2, %5, %5, %3}], [%4];"
                 ::"r"(dst), "l"(tm), "r"(k), "r"(blk16), "r"(bar), "r"(0) : "memory");
}
__device__ __forceinline__ void tma_3d_mc(uint32_t dst, const CUtensorMap* tm, int c0, int c1, int c2, uint32_t bar, uint16_t mask) {
    asm volatile("cp.async.bulk.tensor.3d.shared::cluster.global.mbarrier::complete_tx::bytes.multicast::cluster [%0], [%1, {%2, %3, %4}], [%5], %6;"
                 ::"r"(dst), "l"(tm), "r"(c0), "r"(c1), "r"(c2), "r"(bar), "h"(mask) : "memory");
}
__device__ __forceinline__ void mbar_arrive_cluster(uint32_t bar, uint32_t cta) {
    asm volatile("{\n.reg .b32 ra;\nmapa.shared::cluster.u32 ra, %0, %1;\nmbarrier.arrive.shared::cluster.b64 _, [ra];\n}\n" ::"r"(bar), "r"(cta) : "memory");
}
__device__ __forceinline__ void tma_store_3d(const CUtensorMap* tm, uint32_t src, int c0, int c1, int c2) {
    asm volatile("cp.async.bulk.tensor.3d.global.shared::cta.bulk_group [%0, {%2, %3, %4}], [%1];" ::"l"(tm), "r"(src), "r"(c0), "r"(c1), "r"(c2) : "memory");
}
__device__ __forceinline__ void cluster_arrive() { asm volatile("barrier.cluster.arrive.relaxed.aligned;" ::: "memory"); }
__device__ __forceinline__ void cluster_wait() { asm volatile("barrier.cluster.wait.aligned;" ::: "memory"); }
__device__ __forceinline__ void named_sync(int id, int n) { asm volatile("bar.sync %0, %1;" ::"r"(id), "r"(n) : "memory"); }
__device__ __forceinline__ void flag_add_done(uint32_t* p) {
    asm volatile("fence.proxy.async.global;\nred.release.gpu.global.add.u32 [%0], 1;" ::"l"(p) : "memory");
}
__device__ __forceinline__ void flag_wait(const uint32_t* p, uint32_t target) {
#pragma unroll 1
    for (int i = 0; i < (1 << 22); i++) {
        uint32_t v;
        asm volatile("ld.acquire.gpu.global.u32 %0, [%1];" : "=r"(v) : "l"(p) : "memory");
        if (v >= target) return;
        __nanosleep(20);
    }
    __trap();
}
__device__ __forceinline__ void flag_wait_fast(const uint32_t* p, uint32_t target) {
    uint32_t v0, v1, v2;
    asm volatile("ld.relaxed.gpu.global.u32 %0, [%1];" : "=r"(v0) : "l"(p) : "memory");
    __nanosleep(100);
    asm volatile("ld.relaxed.gpu.global.u32 %0, [%1];" : "=r"(v1) : "l"(p) : "memory");
    __nanosleep(100);
#pragma unroll 1
    for (int i = 0; i < (1 << 22); i++) {
        asm volatile("ld.relaxed.gpu.global.u32 %0, [%1];" : "=r"(v2) : "l"(p) : "memory");
        if (v0 >= target) break;
        asm volatile("ld.relaxed.gpu.global.u32 %0, [%1];" : "=r"(v0) : "l"(p) : "memory");
        if (v1 >= target) break;
        asm volatile("ld.relaxed.gpu.global.u32 %0, [%1];" : "=r"(v1) : "l"(p) : "memory");
        if (v2 >= target) break;
        if (i == (1 << 22) - 1) __trap();
    }
    asm volatile("fence.acquire.gpu;" ::: "memory");
}
__device__ __forceinline__ void flag_wait_head(const uint32_t* base, int h, uint32_t help_target) {
    const uint32_t *p0 = base + (h / 12) * 32, *p1 = base + ((32 + h) / 12) * 32, *p2 = base + ((64 + h) / 12) * 32;
    const uint32_t target = 16;
#pragma unroll 1
    for (int i = 0; i < (1 << 22); i++) {
        uint32_t v0, v1, v2, v3;
        asm volatile("ld.relaxed.gpu.global.u32 %0, [%1];" : "=r"(v3) : "l"(g_flag + F_HELP * 32) : "memory");
        asm volatile("ld.relaxed.gpu.global.u32 %0, [%1];" : "=r"(v0) : "l"(p0) : "memory");
        asm volatile("ld.relaxed.gpu.global.u32 %0, [%1];" : "=r"(v1) : "l"(p1) : "memory");
        asm volatile("ld.relaxed.gpu.global.u32 %0, [%1];" : "=r"(v2) : "l"(p2) : "memory");
        if (v0 >= target && v1 >= target && v2 >= target && v3 >= help_target) { asm volatile("fence.acquire.gpu;" ::: "memory"); return; }
        __nanosleep(40);
    }
    __trap();
}
__device__ __forceinline__ uint32_t ld_relaxed(const uint32_t* p) { uint32_t v; asm volatile("ld.relaxed.gpu.global.u32 %0, [%1];" : "=r"(v) : "l"(p) : "memory"); return v; }
__device__ __forceinline__ float ldcg_f32(const float* p) { float v; asm volatile("ld.global.cg.f32 %0, [%1];" : "=f"(v) : "l"(p) : "memory"); return v; }
__device__ __forceinline__ uint32_t ldcg_u32(const void* p) { uint32_t v; asm volatile("ld.global.cg.b32 %0, [%1];" : "=r"(v) : "l"(p) : "memory"); return v; }
__device__ __forceinline__ void bulk_g2s(uint32_t dst, const void* src, int bytes, uint32_t bar) {
    asm volatile("fence.proxy.async.global;\ncp.async.bulk.shared::cluster.global.mbarrier::complete_tx::bytes [%0], [%1], %2, [%3];"
                 ::"r"(dst), "l"(src), "r"(bytes), "r"(bar) : "memory");
}
__device__ __forceinline__ void bulk_s2g(void* dst, uint32_t src, int bytes) {
    asm volatile("cp.async.bulk.global.shared::cta.bulk_group [%0], [%1], %2;" ::"l"(dst), "r"(src), "r"(bytes) : "memory");
}
__device__ __forceinline__ void bulk_commit() { asm volatile("cp.async.bulk.commit_group;" ::: "memory"); }
__device__ __forceinline__ void bulk_wait_all() { asm volatile("cp.async.bulk.wait_group 0;" ::: "memory"); }
__device__ __forceinline__ void fence_async_smem() { asm volatile("fence.proxy.async.shared::cta;" ::: "memory"); }
__device__ __forceinline__ void stsm4(uint32_t a, uint32_t r0, uint32_t r1, uint32_t r2, uint32_t r3) {
    asm volatile("stmatrix.sync.aligned.m8n8.x4.shared.b16 [%0], {%1,%2,%3,%4};" ::"r"(a), "r"(r0), "r"(r1), "r"(r2), "r"(r3) : "memory");
}
__device__ __forceinline__ void prefetch_tmap(const CUtensorMap* tm) { asm volatile("prefetch.tensormap [%0];" ::"l"(tm) : "memory"); }
__device__ __forceinline__ void wg_fence() { asm volatile("wgmma.fence.sync.aligned;" ::: "memory"); }
__device__ __forceinline__ void wg_commit() { asm volatile("wgmma.commit_group.sync.aligned;" ::: "memory"); }
template <int N> __device__ __forceinline__ void wg_wait() { asm volatile("wgmma.wait_group.sync.aligned %0;" ::"n"(N) : "memory"); }
__host__ __device__ constexpr uint64_t mkdesc(uint32_t addr, uint32_t lbo, uint32_t sbo, uint32_t swz) {
    return (uint64_t)((addr & 0x3FFFF) >> 4) | ((uint64_t)(lbo >> 4) << 16) | ((uint64_t)(sbo >> 4) << 32) | ((uint64_t)swz << 62);
}
template <int N> __device__ __forceinline__ void pin(float (&r)[N]) {
#pragma unroll
    for (int i = 0; i < N; i++) asm volatile("" : "+f"(r[i])::"memory");
}
template <int N> __device__ __forceinline__ void pin(uint32_t (&r)[N]) {
#pragma unroll
    for (int i = 0; i < N; i++) asm volatile("" : "+r"(r[i])::"memory");
}
__device__ __forceinline__ float ex2(float x) { float y; asm("ex2.approx.ftz.f32 %0, %1;" : "=f"(y) : "f"(x)); return y; }
__device__ __forceinline__ uint32_t pack2(float lo, float hi) { uint32_t r; asm("cvt.rn.bf16x2.f32 %0, %1, %2;" : "=r"(r) : "f"(hi), "f"(lo)); return r; }
__device__ __forceinline__ uint32_t hfma2(uint32_t a, uint32_t b, uint32_t c) { uint32_t d; asm("fma.rn.bf16x2 %0, %1, %2, %3;" : "=r"(d) : "r"(a), "r"(b), "r"(c)); return d; }
__device__ __forceinline__ float bf_lo(uint32_t v) { return __uint_as_float(v << 16); }
__device__ __forceinline__ float bf_hi(uint32_t v) { return __uint_as_float(v & 0xffff0000u); }
__device__ __forceinline__ void mma16816(float (&c)[4], uint32_t a0, uint32_t a1, uint32_t a2, uint32_t a3, uint32_t b0, uint32_t b1) {
    asm volatile("mma.sync.aligned.m16n8k16.row.col.f32.bf16.bf16.f32 {%0,%1,%2,%3}, {%4,%5,%6,%7}, {%8,%9}, {%0,%1,%2,%3};"
                 : "+f"(c[0]), "+f"(c[1]), "+f"(c[2]), "+f"(c[3]) : "r"(a0), "r"(a1), "r"(a2), "r"(a3), "r"(b0), "r"(b1));
}
__device__ __forceinline__ void mma1688(float (&c)[4], uint32_t a0, uint32_t a1, uint32_t b0) {
    asm volatile("mma.sync.aligned.m16n8k8.row.col.f32.bf16.bf16.f32 {%0,%1,%2,%3}, {%4,%5}, {%6}, {%0,%1,%2,%3};"
                 : "+f"(c[0]), "+f"(c[1]), "+f"(c[2]), "+f"(c[3]) : "r"(a0), "r"(a1), "r"(b0));
}
__device__ __forceinline__ uint32_t movm_t(uint32_t a) { uint32_t d; asm volatile("movmatrix.sync.aligned.m8n8.trans.b16 %0, %1;" : "=r"(d) : "r"(a)); return d; }
__device__ __forceinline__ void stg128(void* p, uint4 v) { asm volatile("st.global.v4.b32 [%0], {%1,%2,%3,%4};" ::"l"(p), "r"(v.x), "r"(v.y), "r"(v.z), "r"(v.w) : "memory"); }
__device__ __forceinline__ void stg64(void* p, uint32_t a, uint32_t b) { asm volatile("st.global.v2.b32 [%0], {%1,%2};" ::"l"(p), "r"(a), "r"(b) : "memory"); }
__device__ __forceinline__ int frag_pos(int warp4, int lane) { return ((lane & 2) << 5) | (warp4 << 4) | ((lane >> 2) << 1) | (lane & 1); }
__device__ __forceinline__ bool elect_one() {
    uint32_t p;
    asm volatile("{\n.reg .pred p;\nelect.sync _|p, 0xffffffff;\nselp.u32 %0, 1, 0, p;\n}\n" : "=r"(p));
    return p;
}
__device__ __forceinline__ uint32_t clock_lo() { uint32_t v; asm volatile("mov.u32 %0, %%clock;" : "=r"(v)); return v; }
__device__ __forceinline__ int fresh_bid() { int v; asm volatile("mov.u32 %0, %%ctaid.x;" : "=r"(v)); return v; }
__device__ __forceinline__ int fresh_wid() { int v; asm volatile("mov.u32 %0, %%tid.x;" : "=r"(v)); return __shfl_sync(0xffffffffu, v >> 5, 0); }
__device__ __forceinline__ int here(int v) { asm volatile("" : "+r"(v)); return v; }
__device__ __forceinline__ int fresh_tid() { int v; asm volatile("mov.u32 %0, %%tid.x;" : "=r"(v)); return v; }
__device__ __forceinline__ uint32_t lds32(uint32_t a) { uint32_t v; asm volatile("ld.shared.b32 %0, [%1];" : "=r"(v) : "r"(a) : "memory"); return v; }
__device__ __forceinline__ uint4 lds128(uint32_t a) { uint4 v; asm volatile("ld.shared.v4.b32 {%0,%1,%2,%3}, [%4];" : "=r"(v.x), "=r"(v.y), "=r"(v.z), "=r"(v.w) : "r"(a)); return v; }

__device__ __forceinline__ void wgmma_ss128(float (&d)[64], uint64_t da, uint64_t db) {
    asm volatile("{\n.reg .pred p;\nsetp.eq.b32 p, 0, 0;\n"
        "wgmma.mma_async.sync.aligned.m64n128k16.f32.bf16.bf16 "
        "{%0,%1,%2,%3,%4,%5,%6,%7,%8,%9,%10,%11,%12,%13,%14,%15,%16,%17,%18,%19,"
        "%20,%21,%22,%23,%24,%25,%26,%27,%28,%29,%30,%31,%32,%33,%34,%35,%36,%37,%38,%39,"
        "%40,%41,%42,%43,%44,%45,%46,%47,%48,%49,%50,%51,%52,%53,%54,%55,%56,%57,%58,%59,"
        "%60,%61,%62,%63}, "
        "%64, %65, p, 1, 1, 0, 1;\n}\n"
        : "+f"(d[0]), "+f"(d[1]), "+f"(d[2]), "+f"(d[3]), "+f"(d[4]), "+f"(d[5]), "+f"(d[6]), "+f"(d[7]), "+f"(d[8]), "+f"(d[9]),
          "+f"(d[10]), "+f"(d[11]), "+f"(d[12]), "+f"(d[13]), "+f"(d[14]), "+f"(d[15]), "+f"(d[16]), "+f"(d[17]), "+f"(d[18]), "+f"(d[19]),
          "+f"(d[20]), "+f"(d[21]), "+f"(d[22]), "+f"(d[23]), "+f"(d[24]), "+f"(d[25]), "+f"(d[26]), "+f"(d[27]), "+f"(d[28]), "+f"(d[29]),
          "+f"(d[30]), "+f"(d[31]), "+f"(d[32]), "+f"(d[33]), "+f"(d[34]), "+f"(d[35]), "+f"(d[36]), "+f"(d[37]), "+f"(d[38]), "+f"(d[39]),
          "+f"(d[40]), "+f"(d[41]), "+f"(d[42]), "+f"(d[43]), "+f"(d[44]), "+f"(d[45]), "+f"(d[46]), "+f"(d[47]), "+f"(d[48]), "+f"(d[49]),
          "+f"(d[50]), "+f"(d[51]), "+f"(d[52]), "+f"(d[53]), "+f"(d[54]), "+f"(d[55]), "+f"(d[56]), "+f"(d[57]), "+f"(d[58]), "+f"(d[59]),
          "+f"(d[60]), "+f"(d[61]), "+f"(d[62]), "+f"(d[63])
        : "l"(da), "l"(db));
}
__device__ __forceinline__ void wgmma_ss112(float (&d)[56], uint64_t da, uint64_t db) {
    asm volatile("{\n.reg .pred p;\nsetp.eq.b32 p, 0, 0;\n"
        "wgmma.mma_async.sync.aligned.m64n112k16.f32.bf16.bf16 "
        "{%0,%1,%2,%3,%4,%5,%6,%7,%8,%9,%10,%11,%12,%13,%14,%15,%16,%17,%18,%19,"
        "%20,%21,%22,%23,%24,%25,%26,%27,%28,%29,%30,%31,%32,%33,%34,%35,%36,%37,%38,%39,"
        "%40,%41,%42,%43,%44,%45,%46,%47,%48,%49,%50,%51,%52,%53,%54,%55}, "
        "%56, %57, p, 1, 1, 0, 1;\n}\n"
        : "+f"(d[0]), "+f"(d[1]), "+f"(d[2]), "+f"(d[3]), "+f"(d[4]), "+f"(d[5]), "+f"(d[6]), "+f"(d[7]), "+f"(d[8]), "+f"(d[9]),
          "+f"(d[10]), "+f"(d[11]), "+f"(d[12]), "+f"(d[13]), "+f"(d[14]), "+f"(d[15]), "+f"(d[16]), "+f"(d[17]), "+f"(d[18]), "+f"(d[19]),
          "+f"(d[20]), "+f"(d[21]), "+f"(d[22]), "+f"(d[23]), "+f"(d[24]), "+f"(d[25]), "+f"(d[26]), "+f"(d[27]), "+f"(d[28]), "+f"(d[29]),
          "+f"(d[30]), "+f"(d[31]), "+f"(d[32]), "+f"(d[33]), "+f"(d[34]), "+f"(d[35]), "+f"(d[36]), "+f"(d[37]), "+f"(d[38]), "+f"(d[39]),
          "+f"(d[40]), "+f"(d[41]), "+f"(d[42]), "+f"(d[43]), "+f"(d[44]), "+f"(d[45]), "+f"(d[46]), "+f"(d[47]), "+f"(d[48]), "+f"(d[49]),
          "+f"(d[50]), "+f"(d[51]), "+f"(d[52]), "+f"(d[53]), "+f"(d[54]), "+f"(d[55])
        : "l"(da), "l"(db));
}
__device__ __forceinline__ void wgmma_ss128f(float (&d)[64], uint64_t da, uint64_t db) {
    asm volatile("{\n.reg .pred p;\nsetp.ne.b32 p, 0, 0;\n"
        "wgmma.mma_async.sync.aligned.m64n128k16.f32.bf16.bf16 "
        "{%0,%1,%2,%3,%4,%5,%6,%7,%8,%9,%10,%11,%12,%13,%14,%15,%16,%17,%18,%19,"
        "%20,%21,%22,%23,%24,%25,%26,%27,%28,%29,%30,%31,%32,%33,%34,%35,%36,%37,%38,%39,"
        "%40,%41,%42,%43,%44,%45,%46,%47,%48,%49,%50,%51,%52,%53,%54,%55,%56,%57,%58,%59,"
        "%60,%61,%62,%63}, "
        "%64, %65, p, 1, 1, 0, 1;\n}\n"
        : "=f"(d[0]), "=f"(d[1]), "=f"(d[2]), "=f"(d[3]), "=f"(d[4]), "=f"(d[5]), "=f"(d[6]), "=f"(d[7]), "=f"(d[8]), "=f"(d[9]),
          "=f"(d[10]), "=f"(d[11]), "=f"(d[12]), "=f"(d[13]), "=f"(d[14]), "=f"(d[15]), "=f"(d[16]), "=f"(d[17]), "=f"(d[18]), "=f"(d[19]),
          "=f"(d[20]), "=f"(d[21]), "=f"(d[22]), "=f"(d[23]), "=f"(d[24]), "=f"(d[25]), "=f"(d[26]), "=f"(d[27]), "=f"(d[28]), "=f"(d[29]),
          "=f"(d[30]), "=f"(d[31]), "=f"(d[32]), "=f"(d[33]), "=f"(d[34]), "=f"(d[35]), "=f"(d[36]), "=f"(d[37]), "=f"(d[38]), "=f"(d[39]),
          "=f"(d[40]), "=f"(d[41]), "=f"(d[42]), "=f"(d[43]), "=f"(d[44]), "=f"(d[45]), "=f"(d[46]), "=f"(d[47]), "=f"(d[48]), "=f"(d[49]),
          "=f"(d[50]), "=f"(d[51]), "=f"(d[52]), "=f"(d[53]), "=f"(d[54]), "=f"(d[55]), "=f"(d[56]), "=f"(d[57]), "=f"(d[58]), "=f"(d[59]),
          "=f"(d[60]), "=f"(d[61]), "=f"(d[62]), "=f"(d[63])
        : "l"(da), "l"(db));
}
__device__ __forceinline__ void wgmma_ss112f(float (&d)[56], uint64_t da, uint64_t db) {
    asm volatile("{\n.reg .pred p;\nsetp.ne.b32 p, 0, 0;\n"
        "wgmma.mma_async.sync.aligned.m64n112k16.f32.bf16.bf16 "
        "{%0,%1,%2,%3,%4,%5,%6,%7,%8,%9,%10,%11,%12,%13,%14,%15,%16,%17,%18,%19,"
        "%20,%21,%22,%23,%24,%25,%26,%27,%28,%29,%30,%31,%32,%33,%34,%35,%36,%37,%38,%39,"
        "%40,%41,%42,%43,%44,%45,%46,%47,%48,%49,%50,%51,%52,%53,%54,%55}, "
        "%56, %57, p, 1, 1, 0, 1;\n}\n"
        : "=f"(d[0]), "=f"(d[1]), "=f"(d[2]), "=f"(d[3]), "=f"(d[4]), "=f"(d[5]), "=f"(d[6]), "=f"(d[7]), "=f"(d[8]), "=f"(d[9]),
          "=f"(d[10]), "=f"(d[11]), "=f"(d[12]), "=f"(d[13]), "=f"(d[14]), "=f"(d[15]), "=f"(d[16]), "=f"(d[17]), "=f"(d[18]), "=f"(d[19]),
          "=f"(d[20]), "=f"(d[21]), "=f"(d[22]), "=f"(d[23]), "=f"(d[24]), "=f"(d[25]), "=f"(d[26]), "=f"(d[27]), "=f"(d[28]), "=f"(d[29]),
          "=f"(d[30]), "=f"(d[31]), "=f"(d[32]), "=f"(d[33]), "=f"(d[34]), "=f"(d[35]), "=f"(d[36]), "=f"(d[37]), "=f"(d[38]), "=f"(d[39]),
          "=f"(d[40]), "=f"(d[41]), "=f"(d[42]), "=f"(d[43]), "=f"(d[44]), "=f"(d[45]), "=f"(d[46]), "=f"(d[47]), "=f"(d[48]), "=f"(d[49]),
          "=f"(d[50]), "=f"(d[51]), "=f"(d[52]), "=f"(d[53]), "=f"(d[54]), "=f"(d[55])
        : "l"(da), "l"(db));
}
__device__ __forceinline__ void wgmma_rs80(float (&d)[40], uint32_t a0, uint32_t a1, uint32_t a2, uint32_t a3, uint64_t db) {
    asm volatile("{\n.reg .pred p;\nsetp.eq.b32 p, 0, 0;\n"
        "wgmma.mma_async.sync.aligned.m64n80k16.f32.bf16.bf16 "
        "{%0,%1,%2,%3,%4,%5,%6,%7,%8,%9,%10,%11,%12,%13,%14,%15,%16,%17,%18,%19,"
        "%20,%21,%22,%23,%24,%25,%26,%27,%28,%29,%30,%31,%32,%33,%34,%35,%36,%37,%38,%39}, "
        "{%40,%41,%42,%43}, %44, p, 1, 1, 1;\n}\n"
        : "+f"(d[0]), "+f"(d[1]), "+f"(d[2]), "+f"(d[3]), "+f"(d[4]), "+f"(d[5]), "+f"(d[6]), "+f"(d[7]), "+f"(d[8]), "+f"(d[9]),
          "+f"(d[10]), "+f"(d[11]), "+f"(d[12]), "+f"(d[13]), "+f"(d[14]), "+f"(d[15]), "+f"(d[16]), "+f"(d[17]), "+f"(d[18]), "+f"(d[19]),
          "+f"(d[20]), "+f"(d[21]), "+f"(d[22]), "+f"(d[23]), "+f"(d[24]), "+f"(d[25]), "+f"(d[26]), "+f"(d[27]), "+f"(d[28]), "+f"(d[29]),
          "+f"(d[30]), "+f"(d[31]), "+f"(d[32]), "+f"(d[33]), "+f"(d[34]), "+f"(d[35]), "+f"(d[36]), "+f"(d[37]), "+f"(d[38]), "+f"(d[39])
        : "r"(a0), "r"(a1), "r"(a2), "r"(a3), "l"(db));
}
__device__ __forceinline__ void wgmma_rs80f(float (&d)[40], uint32_t a0, uint32_t a1, uint32_t a2, uint32_t a3, uint64_t db) {
    asm volatile("{\n.reg .pred p;\nsetp.ne.b32 p, 0, 0;\n"
        "wgmma.mma_async.sync.aligned.m64n80k16.f32.bf16.bf16 "
        "{%0,%1,%2,%3,%4,%5,%6,%7,%8,%9,%10,%11,%12,%13,%14,%15,%16,%17,%18,%19,"
        "%20,%21,%22,%23,%24,%25,%26,%27,%28,%29,%30,%31,%32,%33,%34,%35,%36,%37,%38,%39}, "
        "{%40,%41,%42,%43}, %44, p, 1, 1, 1;\n}\n"
        : "=f"(d[0]), "=f"(d[1]), "=f"(d[2]), "=f"(d[3]), "=f"(d[4]), "=f"(d[5]), "=f"(d[6]), "=f"(d[7]), "=f"(d[8]), "=f"(d[9]),
          "=f"(d[10]), "=f"(d[11]), "=f"(d[12]), "=f"(d[13]), "=f"(d[14]), "=f"(d[15]), "=f"(d[16]), "=f"(d[17]), "=f"(d[18]), "=f"(d[19]),
          "=f"(d[20]), "=f"(d[21]), "=f"(d[22]), "=f"(d[23]), "=f"(d[24]), "=f"(d[25]), "=f"(d[26]), "=f"(d[27]), "=f"(d[28]), "=f"(d[29]),
          "=f"(d[30]), "=f"(d[31]), "=f"(d[32]), "=f"(d[33]), "=f"(d[34]), "=f"(d[35]), "=f"(d[36]), "=f"(d[37]), "=f"(d[38]), "=f"(d[39])
        : "r"(a0), "r"(a1), "r"(a2), "r"(a3), "l"(db));
}
__device__ __forceinline__ void wgmma_qk0(float (&d)[32], uint32_t a0, uint32_t a1, uint32_t a2, uint32_t a3, uint64_t db) {
    asm volatile("{\n.reg .pred p;\nsetp.ne.b32 p, 0, 0;\n"
        "wgmma.mma_async.sync.aligned.m64n64k16.f32.bf16.bf16 "
        "{%0,%1,%2,%3,%4,%5,%6,%7,%8,%9,%10,%11,%12,%13,%14,%15,%16,%17,%18,%19,"
        "%20,%21,%22,%23,%24,%25,%26,%27,%28,%29,%30,%31}, "
        "{%32,%33,%34,%35}, %36, p, 1, 1, 0;\n}\n"
        : "=f"(d[0]), "=f"(d[1]), "=f"(d[2]), "=f"(d[3]), "=f"(d[4]), "=f"(d[5]), "=f"(d[6]), "=f"(d[7]), "=f"(d[8]), "=f"(d[9]),
          "=f"(d[10]), "=f"(d[11]), "=f"(d[12]), "=f"(d[13]), "=f"(d[14]), "=f"(d[15]), "=f"(d[16]), "=f"(d[17]), "=f"(d[18]), "=f"(d[19]),
          "=f"(d[20]), "=f"(d[21]), "=f"(d[22]), "=f"(d[23]), "=f"(d[24]), "=f"(d[25]), "=f"(d[26]), "=f"(d[27]), "=f"(d[28]), "=f"(d[29]),
          "=f"(d[30]), "=f"(d[31])
        : "r"(a0), "r"(a1), "r"(a2), "r"(a3), "l"(db));
}
__device__ __forceinline__ void wgmma_qk1(float (&d)[32], uint32_t a0, uint32_t a1, uint32_t a2, uint32_t a3, uint64_t db) {
    asm volatile("{\n.reg .pred p;\nsetp.eq.b32 p, 0, 0;\n"
        "wgmma.mma_async.sync.aligned.m64n64k16.f32.bf16.bf16 "
        "{%0,%1,%2,%3,%4,%5,%6,%7,%8,%9,%10,%11,%12,%13,%14,%15,%16,%17,%18,%19,"
        "%20,%21,%22,%23,%24,%25,%26,%27,%28,%29,%30,%31}, "
        "{%32,%33,%34,%35}, %36, p, 1, 1, 0;\n}\n"
        : "+f"(d[0]), "+f"(d[1]), "+f"(d[2]), "+f"(d[3]), "+f"(d[4]), "+f"(d[5]), "+f"(d[6]), "+f"(d[7]), "+f"(d[8]), "+f"(d[9]),
          "+f"(d[10]), "+f"(d[11]), "+f"(d[12]), "+f"(d[13]), "+f"(d[14]), "+f"(d[15]), "+f"(d[16]), "+f"(d[17]), "+f"(d[18]), "+f"(d[19]),
          "+f"(d[20]), "+f"(d[21]), "+f"(d[22]), "+f"(d[23]), "+f"(d[24]), "+f"(d[25]), "+f"(d[26]), "+f"(d[27]), "+f"(d[28]), "+f"(d[29]),
          "+f"(d[30]), "+f"(d[31])
        : "r"(a0), "r"(a1), "r"(a2), "r"(a3), "l"(db));
}
__device__ __forceinline__ void wgmma_pv(float (&d)[12], uint32_t a0, uint32_t a1, uint32_t a2, uint32_t a3, uint64_t db) {
    asm volatile("{\n.reg .pred p;\nsetp.eq.b32 p, 0, 0;\n"
        "wgmma.mma_async.sync.aligned.m64n24k16.f32.bf16.bf16 "
        "{%0,%1,%2,%3,%4,%5,%6,%7,%8,%9,%10,%11}, "
        "{%12,%13,%14,%15}, %16, p, 1, 1, 1;\n}\n"
        : "+f"(d[0]), "+f"(d[1]), "+f"(d[2]), "+f"(d[3]), "+f"(d[4]), "+f"(d[5]), "+f"(d[6]), "+f"(d[7]), "+f"(d[8]), "+f"(d[9]),
          "+f"(d[10]), "+f"(d[11])
        : "r"(a0), "r"(a1), "r"(a2), "r"(a3), "l"(db));
}
__device__ __forceinline__ void wgmma_pvn(float (&d)[12], uint32_t a0, uint32_t a1, uint32_t a2, uint32_t a3, uint64_t db) {
    asm volatile("{\n.reg .pred p;\nsetp.eq.b32 p, 0, 0;\n"
        "wgmma.mma_async.sync.aligned.m64n24k16.f32.bf16.bf16 "
        "{%0,%1,%2,%3,%4,%5,%6,%7,%8,%9,%10,%11}, "
        "{%12,%13,%14,%15}, %16, p, -1, 1, 1;\n}\n"
        : "+f"(d[0]), "+f"(d[1]), "+f"(d[2]), "+f"(d[3]), "+f"(d[4]), "+f"(d[5]), "+f"(d[6]), "+f"(d[7]), "+f"(d[8]), "+f"(d[9]),
          "+f"(d[10]), "+f"(d[11])
        : "r"(a0), "r"(a1), "r"(a2), "r"(a3), "l"(db));
}
__device__ __forceinline__ void wgmma_pv0(float (&d)[12], uint32_t a0, uint32_t a1, uint32_t a2, uint32_t a3, uint64_t db) {
    asm volatile("{\n.reg .pred p;\nsetp.ne.b32 p, 0, 0;\n"
        "wgmma.mma_async.sync.aligned.m64n24k16.f32.bf16.bf16 "
        "{%0,%1,%2,%3,%4,%5,%6,%7,%8,%9,%10,%11}, "
        "{%12,%13,%14,%15}, %16, p, 1, 1, 1;\n}\n"
        : "=f"(d[0]), "=f"(d[1]), "=f"(d[2]), "=f"(d[3]), "=f"(d[4]), "=f"(d[5]), "=f"(d[6]), "=f"(d[7]), "=f"(d[8]), "=f"(d[9]),
          "=f"(d[10]), "=f"(d[11])
        : "r"(a0), "r"(a1), "r"(a2), "r"(a3), "l"(db));
}
__device__ __forceinline__ void wgmma_l64a(float (&d)[32], uint64_t da, uint64_t db) {
    asm volatile("{\n.reg .pred p;\nsetp.ne.b32 p, 0, 0;\n"
        "wgmma.mma_async.sync.aligned.m64n64k16.f32.bf16.bf16 "
        "{%0,%1,%2,%3,%4,%5,%6,%7,%8,%9,%10,%11,%12,%13,%14,%15,%16,%17,%18,%19,"
        "%20,%21,%22,%23,%24,%25,%26,%27,%28,%29,%30,%31}, "
        "%32, %33, p, 1, 1, 0, 0;\n}\n"
        : "=f"(d[0]), "=f"(d[1]), "=f"(d[2]), "=f"(d[3]), "=f"(d[4]), "=f"(d[5]), "=f"(d[6]), "=f"(d[7]), "=f"(d[8]), "=f"(d[9]),
          "=f"(d[10]), "=f"(d[11]), "=f"(d[12]), "=f"(d[13]), "=f"(d[14]), "=f"(d[15]), "=f"(d[16]), "=f"(d[17]), "=f"(d[18]), "=f"(d[19]),
          "=f"(d[20]), "=f"(d[21]), "=f"(d[22]), "=f"(d[23]), "=f"(d[24]), "=f"(d[25]), "=f"(d[26]), "=f"(d[27]), "=f"(d[28]), "=f"(d[29]),
          "=f"(d[30]), "=f"(d[31])
        : "l"(da), "l"(db));
}
__device__ __forceinline__ void wgmma_l64b(float (&d)[32], uint64_t da, uint64_t db) {
    asm volatile("{\n.reg .pred p;\nsetp.eq.b32 p, 0, 0;\n"
        "wgmma.mma_async.sync.aligned.m64n64k16.f32.bf16.bf16 "
        "{%0,%1,%2,%3,%4,%5,%6,%7,%8,%9,%10,%11,%12,%13,%14,%15,%16,%17,%18,%19,"
        "%20,%21,%22,%23,%24,%25,%26,%27,%28,%29,%30,%31}, "
        "%32, %33, p, 1, 1, 0, 0;\n}\n"
        : "+f"(d[0]), "+f"(d[1]), "+f"(d[2]), "+f"(d[3]), "+f"(d[4]), "+f"(d[5]), "+f"(d[6]), "+f"(d[7]), "+f"(d[8]), "+f"(d[9]),
          "+f"(d[10]), "+f"(d[11]), "+f"(d[12]), "+f"(d[13]), "+f"(d[14]), "+f"(d[15]), "+f"(d[16]), "+f"(d[17]), "+f"(d[18]), "+f"(d[19]),
          "+f"(d[20]), "+f"(d[21]), "+f"(d[22]), "+f"(d[23]), "+f"(d[24]), "+f"(d[25]), "+f"(d[26]), "+f"(d[27]), "+f"(d[28]), "+f"(d[29]),
          "+f"(d[30]), "+f"(d[31])
        : "l"(da), "l"(db));
}
__device__ __forceinline__ void wgmma_l16a(float (&d)[8], uint64_t da, uint64_t db) {
    asm volatile("{\n.reg .pred p;\nsetp.ne.b32 p, 0, 0;\n"
        "wgmma.mma_async.sync.aligned.m64n16k16.f32.bf16.bf16 "
        "{%0,%1,%2,%3,%4,%5,%6,%7}, "
        "%8, %9, p, 1, 1, 0, 0;\n}\n"
        : "=f"(d[0]), "=f"(d[1]), "=f"(d[2]), "=f"(d[3]), "=f"(d[4]), "=f"(d[5]), "=f"(d[6]), "=f"(d[7])
        : "l"(da), "l"(db));
}
__device__ __forceinline__ void wgmma_l16b(float (&d)[8], uint64_t da, uint64_t db) {
    asm volatile("{\n.reg .pred p;\nsetp.eq.b32 p, 0, 0;\n"
        "wgmma.mma_async.sync.aligned.m64n16k16.f32.bf16.bf16 "
        "{%0,%1,%2,%3,%4,%5,%6,%7}, "
        "%8, %9, p, 1, 1, 0, 0;\n}\n"
        : "+f"(d[0]), "+f"(d[1]), "+f"(d[2]), "+f"(d[3]), "+f"(d[4]), "+f"(d[5]), "+f"(d[6]), "+f"(d[7])
        : "l"(da), "l"(db));
}

__device__ __forceinline__ uint32_t exp2_pair_fma(float a, float b) {
    const uint32_t y = __byte_perm(__float_as_uint(a), __float_as_uint(b), 0x6521);
    const uint32_t z = 0xFE7BFE7Bu - y;
    const uint32_t e = hfma2(y, z, 0x3F053F05u);
    return hfma2(y, e, y);
}
__device__ __forceinline__ void qk_tile(float (&s)[32], const uint32_t (&q)[8], uint64_t dk0, uint64_t dk1) {
    wgmma_qk0(s, q[0], q[1], q[2], q[3], dk0);
    wgmma_qk1(s, q[4], q[5], q[6], q[7], dk1);
}
__device__ __forceinline__ void exp_pv_tile(const float (&s)[32], uint32_t (&p)[16], float (&o)[12], uint64_t dv, const int mask) {
    auto ex = [&](int j) {
        if ((mask >> (j >> 1)) & 1) { p[2 * j] = exp2_pair_fma(s[4 * j], s[4 * j + 1]); p[2 * j + 1] = exp2_pair_fma(s[4 * j + 2], s[4 * j + 3]); }
        else { p[2 * j] = pack2(ex2(s[4 * j]), ex2(s[4 * j + 1])); p[2 * j + 1] = pack2(ex2(s[4 * j + 2]), ex2(s[4 * j + 3])); }
    };
    auto pv = [&](int k) {
        if ((mask >> k) & 1) wgmma_pvn(o, p[4 * k], p[4 * k + 1], p[4 * k + 2], p[4 * k + 3], dv + k * 48);
        else wgmma_pv(o, p[4 * k], p[4 * k + 1], p[4 * k + 2], p[4 * k + 3], dv + k * 48);
    };
    auto hold = [&](int j) { asm volatile("" : "+r"(p[2 * j]), "+r"(p[2 * j + 1])::"memory"); };
    ex(2); ex(0); ex(1); hold(2);
    wg_fence(); pv(0);
    ex(3); ex(4); ex(5); ex(6); ex(7);
    wg_fence(); pv(1); pv(2); pv(3);
    wg_commit();
}
__device__ __forceinline__ void finish_o(const float (&o)[12], uint32_t (&w)[6], int odd, float g0, float g1, int lane, float& l0, float& l1) {
    const int src = (lane & ~3) | (odd ? 0 : 2);
    l0 = __shfl_sync(0xffffffffu, o[8], src);
    l1 = __shfl_sync(0xffffffffu, o[10], src);
    float r0, r1;
    asm("rcp.approx.ftz.f32 %0, %1;" : "=f"(r0) : "f"(l0));
    asm("rcp.approx.ftz.f32 %0, %1;" : "=f"(r1) : "f"(l1));
    const float f0 = g0 * r0, f1 = g1 * r1;
#pragma unroll
    for (int d = 0; d < 3; d++) { w[2 * d] = pack2(o[4 * d] * f0, o[4 * d + 1] * f0); w[2 * d + 1] = pack2(o[4 * d + 2] * f1, o[4 * d + 3] * f1); }
}
struct OutPtr { uint8_t *p01, *p2; bool has2; };
__device__ __forceinline__ OutPtr out_ptr(uint32_t row16, uint32_t h, uint32_t gbase, uint32_t lane) {
    uint8_t* base = reinterpret_cast<uint8_t*>(g_att) + ((row16 >> 2) * 163840u + gbase * 1024u + h * 2560u + (row16 & 3) * 128u);
    const uint32_t pos = (lane >> 2) * 16 + (lane & 1) * 8, odd = h & 1, hi = (lane >> 1) & 1;
    return {base + (pos + (hi + odd) * 512), base + (pos + (odd ? 0 : 2048)), hi == odd};
}
__device__ __forceinline__ void store_o(const uint32_t (&w)[6], const OutPtr& o, int off) {
    stg64(o.p01 + off, w[0], w[1]);
    stg64(o.p01 + off + 1024, w[2], w[3]);
    if (o.has2) stg64(o.p2 + off, w[4], w[5]);
}

__device__ __forceinline__ int p1_mp(int bid) { return (bid >> 1) & 7; }
__device__ __forceinline__ int p1_nt(int bid) { return bid >> 4; }
__device__ __forceinline__ int p1_nta(int nt) { return (nt + 3) & 7; }
constexpr uint32_t PACE = 300, G1 = 500, G2 = 1200;
constexpr int LJ = 16;
constexpr uint32_t SB0 = 1024;
constexpr int SLOT = 24576;
constexpr int OFF_X = 98304, OFF_R = 6 * SLOT, OFF_L = OFF_R - 1536, OFF_BAR = 9 * SLOT;
constexpr int OFF_F = OFF_BAR + 1024 + 128, SMEM_BYTES = OFF_F + 8192;
enum { B_FULL = 0, B_EMPTY = 48, B_STGB = 96, B_STGA = 104, B_RET = 112, B_NRM = 144, B_HLP = 152, B_KV = 160, B_HDR = 192, B_L = 200, B_WO = 208, B_XCH = 248, B_AF = 264, B_LD = 328, B_R26 = 336, B_AE = 344, B_W0 = 376, B_ZERO = 400, B_MISC = 416, B_PUB = 1024 };
__host__ __device__ constexpr int k_off(int j) {
    return j < 8 ? (7 + (j >> 2)) * SLOT + (j & 3) * 3072 : j == 8 ? OFF_R - 6144 : j < 20 ? 3 * SLOT + (j - 9) * 3072 : j < 26 ? 36864 + (j - 20) * 3072 : (j - 26) * 3072;
}
__host__ __device__ constexpr int v_off(int j) { return k_off(j) + (j < 8 ? 4 : j == 8 ? 1 : j < 20 ? 11 : 6) * 3072; }
__host__ __device__ constexpr int wo_off(int i) { return 3 * SLOT + (i < 7 ? i : i - 7) * 20480; }
__host__ __device__ constexpr int wo_bar(int i) { return i < 3 ? 0 : i < 7 ? 1 : i - 5; }
constexpr float SCORE_LIMIT2 = 118.f * 118.f;

__device__ __forceinline__ void load_kv(uint32_t sb, int h, int i, int j0, int n, int arm) {
    const uint32_t bar = sb + OFF_BAR + B_KV + 8 * i;
    if (arm) mbar_expect_tx(bar, arm * 6144);
    bulk_g2s(sb + k_off(j0), g_qkv + (size_t)(32 + h) * HEAD_BYTES + j0 * 3072, n * 3072, bar);
    bulk_g2s(sb + v_off(j0), g_qkv + (size_t)(64 + h) * HEAD_BYTES + j0 * 3072, n * 3072, bar);
}
__device__ __forceinline__ void load_wo(uint32_t sb, int seq, int n) {
    const uint32_t bar = sb + OFF_BAR + B_WO + 8 * wo_bar(seq);
    mbar_expect_tx(bar, n * 20480);
    bulk_g2s(sb + wo_off(seq), reinterpret_cast<const uint8_t*>(g_wo) + (blockIdx.x & 7) * 204800 + seq * 20480, n * 20480, bar);
}

__device__ __forceinline__ void local_attn(uint32_t sb, uint32_t wid, uint64_t dK0, uint64_t dK1, uint64_t dV) {
    const uint32_t tid = fresh_tid(), lane = tid & 31, g = lane >> 2, t2 = (lane & 3) * 2;
    const uint32_t wg = wid >> 2, w = wid & 3;
    const uint32_t bid = fresh_bid(), h = bid >> 2, qb = bid & 3;
    const float* gp = g_gate + (qb * 512 + wg * 128 + w * 16) + g;
    const float gt[4] = {ldcg_f32(gp), ldcg_f32(gp + 8), ldcg_f32(gp + 64), ldcg_f32(gp + 72)};
    const bool cur0 = t2 <= g, cur1 = t2 < g;
    mbar_wait(sb + OFF_BAR + B_L, 0);
    const uint32_t mc = (cur0 ? 0xffffu : 0u) | (cur1 ? 0xffff0000u : 0u);
    uint32_t mk[5];
    float v0[4], v1[4];
    {
        const uint64_t dq0 = dK0 + ((OFF_L >> 4) + wg * 384), dq1 = dK1 + ((OFF_L >> 4) + wg * 384);
        float sa[2][32], sc[2][8];
        wg_fence();
#pragma unroll
        for (int b = 0; b < 2; b++) {
            wgmma_l64a(sa[b], dq0 + b * 192, dq0 + b * 192 + (24576 >> 4)); wgmma_l64b(sa[b], dq1 + b * 192, dq1 + b * 192 + (24576 >> 4));
            wgmma_l16a(sc[b], dq0 + b * 192, dq0 + b * 192 + (27648 >> 4)); wgmma_l16b(sc[b], dq1 + b * 192, dq1 + b * 192 + (27648 >> 4));
        }
        wg_commit(); wg_wait<0>(); pin(sa[0]); pin(sa[1]); pin(sc[0]); pin(sc[1]);
#define LS(B, BLK, R, E) ((BLK) < 4 ? sa[B][((BLK) * 8 + (R) * 6 + (E)) & 31] : sc[B][(R) * 6 + (E)])
#define LWIN(W) { _Pragma("unroll") for (int i = 0; i < 4; i++) { v0[i] = cur0 ? LS(i >> 1, (W) + 1, i & 1, 0) : LS(i >> 1, W, i & 1, 0); \
                                                                 v1[i] = cur1 ? LS(i >> 1, (W) + 1, i & 1, 1) : LS(i >> 1, W, i & 1, 1); } \
                  _Pragma("unroll") for (int ks = 0; ks < 5; ks++) mk[ks] = ks == (W) ? ~mc : ks == (W) + 1 ? mc : 0u; pin(mk); }
        if (w == 0) LWIN(0) else if (w == 1) LWIN(1) else if (w == 2) LWIN(2) else LWIN(3)
#undef LWIN
#undef LS
    }
    if (qb == 0 && wid == 0) {
        if (!cur0) v0[0] = v0[1] = -INFINITY;
        if (!cur1) v1[0] = v1[1] = -INFINITY;
    }
    float m[4], l[4];
#pragma unroll
    for (int i = 0; i < 4; i++) m[i] = fmaxf(v0[i], v1[i]);
#pragma unroll
    for (int i = 0; i < 4; i++) m[i] = fmaxf(m[i], __shfl_xor_sync(0xffffffffu, m[i], 1));
#pragma unroll
    for (int i = 0; i < 4; i++) m[i] = fmaxf(m[i], __shfl_xor_sync(0xffffffffu, m[i], 2));
#pragma unroll
    for (int i = 0; i < 4; i++) { v0[i] = ex2(v0[i] - m[i]); v1[i] = ex2(v1[i] - m[i]); l[i] = v0[i] + v1[i]; }
#pragma unroll
    for (int i = 0; i < 4; i++) l[i] += __shfl_xor_sync(0xffffffffu, l[i], 1);
#pragma unroll
    for (int i = 0; i < 4; i++) l[i] += __shfl_xor_sync(0xffffffffu, l[i], 2);
    uint32_t pp[4];
#pragma unroll
    for (int i = 0; i < 4; i++) {
        float r;
        asm("rcp.approx.ftz.f32 %0, %1;" : "=f"(r) : "f"(l[i]));
        r *= gt[i];
        pp[i] = pack2(v0[i] * r, v1[i] * r);
    }
    uint32_t p[2][20];
#pragma unroll
    for (int ks = 0; ks < 5; ks++) {
#pragma unroll
        for (int b = 0; b < 2; b++) { p[b][4 * ks] = pp[2 * b] & mk[ks]; p[b][4 * ks + 1] = p[b][4 * ks + 2] = 0u; p[b][4 * ks + 3] = pp[2 * b + 1] & mk[ks]; }
    }
    pin(p[0]); pin(p[1]);
    const uint64_t dv = dV + (((OFF_L + 24576 + 25344) >> 4) + wg * 384);
    float o[2][12];
    wg_fence();
#pragma unroll
    for (int b = 0; b < 2; b++) {
        wgmma_pv0(o[b], p[b][0], p[b][1], p[b][2], p[b][3], dv + b * 192);
#pragma unroll
        for (int ks = 1; ks < 5; ks++) wgmma_pv(o[b], p[b][4 * ks], p[b][4 * ks + 1], p[b][4 * ks + 2], p[b][4 * ks + 3], dv + b * 192 + ks * 48);
    }
    wg_commit();
    const OutPtr op = out_ptr(qb * 32 + wg * 8 + w, h, 0, lane);
    wg_wait<0>(); pin(o[0]); pin(o[1]);
#pragma unroll
    for (int b = 0; b < 2; b++) {
        uint32_t wv[6];
#pragma unroll
        for (int i = 0; i < 6; i++) wv[i] = pack2(o[b][2 * i], o[b][2 * i + 1]);
        store_o(wv, op, b * 163840);
    }
    __syncwarp();
    if (elect_one()) mbar_arrive(sb + OFF_BAR + B_LD);
}

__device__ __noinline__ void exact_rows(int h, int row16, int lane) {
    const bool aug_lane = ((lane & 3) >= 2) != ((h & 1) != 0);
    const uint8_t* a = g_qkv + (size_t)h * HEAD_BYTES + row16 * 768 + lane * 4;
    const uint8_t* gk = g_qkv + (size_t)(32 + h) * HEAD_BYTES + lane * 4;
    const uint8_t* gv = g_qkv + (size_t)(64 + h) * HEAD_BYTES + lane * 4;
    const uint32_t q0 = ldcg_u32(a), q1 = ldcg_u32(a + 384), q2 = ldcg_u32(a + 128), q3 = ldcg_u32(a + 512);
    const uint32_t q4 = aug_lane ? 0u : ldcg_u32(a + 256), q5 = aug_lane ? 0u : ldcg_u32(a + 640);
    float m0 = -INFINITY, m1 = -INFINITY;
#pragma unroll 4
    for (int kg = 0; kg < 256; kg++) {
        const uint8_t* ka = gk + kg * 384;
        float c[4] = {0.f, 0.f, 0.f, 0.f};
        mma16816(c, q0, q1, q2, q3, ldcg_u32(ka), ldcg_u32(ka + 128));
        mma1688(c, q4, q5, ldcg_u32(ka + 256));
        m0 = fmaxf(m0, fmaxf(c[0], c[1])); m1 = fmaxf(m1, fmaxf(c[2], c[3]));
    }
    m0 = fmaxf(m0, __shfl_xor_sync(0xffffffffu, m0, 1)); m1 = fmaxf(m1, __shfl_xor_sync(0xffffffffu, m1, 1));
    m0 = fmaxf(m0, __shfl_xor_sync(0xffffffffu, m0, 2)); m1 = fmaxf(m1, __shfl_xor_sync(0xffffffffu, m1, 2));
    float oc[3][4];
#pragma unroll
    for (int d = 0; d < 3; d++) oc[d][0] = oc[d][1] = oc[d][2] = oc[d][3] = 0.f;
#pragma unroll 2
    for (int kg = 0; kg < 256; kg += 2) {
        uint32_t kk[2][3], vv[2][3], pp[2][2];
#pragma unroll
        for (int e = 0; e < 2; e++)
#pragma unroll
            for (int d = 0; d < 3; d++) { kk[e][d] = ldcg_u32(gk + (kg + e) * 384 + d * 128); vv[e][d] = ldcg_u32(gv + (kg + e) * 384 + d * 128); }
#pragma unroll
        for (int e = 0; e < 2; e++) {
            float c[4] = {0.f, 0.f, 0.f, 0.f};
            mma16816(c, q0, q1, q2, q3, kk[e][0], kk[e][1]);
            mma1688(c, q4, q5, kk[e][2]);
            pp[e][0] = pack2(ex2(c[0] - m0), ex2(c[1] - m0));
            pp[e][1] = pack2(ex2(c[2] - m1), ex2(c[3] - m1));
        }
#pragma unroll
        for (int d = 0; d < 3; d++) mma16816(oc[d], pp[0][0], pp[0][1], pp[1][0], pp[1][1], movm_t(vv[0][d]), movm_t(vv[1][d]));
    }
    float o[12];
#pragma unroll
    for (int i = 0; i < 12; i++) o[i] = oc[i >> 2][i & 3];
    const int row = row16 * 16 + (lane >> 2);
    float l0, l1;
    uint32_t w[6];
    finish_o(o, w, h & 1, 1.f - ldcg_f32(g_gate + row), 1.f - ldcg_f32(g_gate + row + 8), lane, l0, l1);
    store_o(w, out_ptr(row16, h, 80, lane), 0);
}


__device__ __forceinline__ uint32_t frag_off(int mh, int item) {
    return item < 5 ? 40960 + (mh * 2 + item) * 8192 : (item == 9 && mh) ? OFF_F : mh * 40960 + (item - 5) * 8192;
}
__device__ __forceinline__ void load_frag(uint32_t sb, int bid, int mh, int part) {
    const uint32_t fb = sb + OFF_BAR + B_AF + mh * 32 + part * 8;
    const uint2* src = g_att + (((bid >> 5) * 8 + mh * 4 + ((bid >> 3) & 3)) * 160 + (bid & 1) * 40 + (part ? 64 + part * 16 : 0)) * 128;
    if (part == 0) mbar_expect_tx(fb, 16384);
    bulk_g2s(sb + frag_off(mh, part ? 3 + 2 * part : 0), src, (part == 2 && !mh) ? 24576 : 16384, fb);
    if (part == 2 && mh) bulk_g2s(sb + OFF_F, src + 2048, 8192, fb);
}
__device__ __forceinline__ uint32_t* atta_out(int bid) { return g_flag + (F_ATTA + (bid & 3) * 2 + (bid >> 6)) * 32; }
__device__ __forceinline__ uint32_t* attb_out(int bid, int wg) { return g_flag + (F_ATTB + ((bid & 3) * 4 + wg) * 2 + (bid >> 6)) * 32; }
__device__ __forceinline__ uint32_t* atta_in(int bid) { return g_flag + (F_ATTA + (bid >> 5) * 2 + (bid & 1)) * 32; }
__device__ __forceinline__ uint32_t* attb_in(int bid) { return g_flag + (F_ATTB + (bid >> 3) * 2 + (bid & 1)) * 32; }
__device__ __forceinline__ void service(uint32_t sb, int step, uint32_t aflag) {
    const uint32_t bars = sb + OFF_BAR;
    const int bid = fresh_bid(), h = bid >> 2, qb = bid & 3;
    if (step == 0) {
        bulk_wait_all();
        flag_add_done(g_flag + (F_QKVA + p1_nta(p1_nt(bid))) * 32);
        load_kv(sb, h, 3, 20, 6, 12); load_kv(sb, h, 3, 26, 6, 0);
    } else if (step == 3) {
        mbar_wait(bars + B_RET + 24, 0);
        load_wo(sb, 0, 3); load_wo(sb, 3, 4);
    } else if (step == 4) {
        mbar_wait(bars + B_LD, 0);
        flag_add_done(atta_out(bid));
    } else if (step == 2) {
        if (aflag >= 16) {
            mbar_wait(bars + B_R26, 0);
            asm volatile("fence.acquire.gpu;" ::: "memory");
            load_frag(sb, bid, 0, 0); load_frag(sb, bid, 1, 0);
        }
    } else {
        mbar_wait(bars + B_RET, 0);
        fence_async_smem();
        const int halo = qb ? 768 : 0;
        const uint8_t* src = g_qkv + (size_t)(96 + h) * HEAD_BYTES + qb * 24576;
        mbar_expect_tx(bars + B_L, 3 * 24576 + 2 * halo);
        bulk_g2s(sb + OFF_L, src, 24576, bars + B_L);
        bulk_g2s(sb + OFF_L + 24576 + 768 - halo, src + (size_t)32 * HEAD_BYTES - halo, 24576 + halo, bars + B_L);
        bulk_g2s(sb + OFF_L + 24576 + 25344 + 768 - halo, src + (size_t)64 * HEAD_BYTES - halo, 24576 + halo, bars + B_L);
    }
}

__global__ void __cluster_dims__(2, 1, 1) __launch_bounds__(512, 1)
k_fused(const __grid_constant__ CUtensorMap tmX, const __grid_constant__ CUtensorMap tmWb, const __grid_constant__ CUtensorMap tmWa,
        const __grid_constant__ CUtensorMap tmS, const __nv_bfloat16* __restrict__ x, const __nv_bfloat16* __restrict__ gate_w,
        const uint8_t* __restrict__ wb, const uint8_t* __restrict__ woa, const uint8_t* __restrict__ wob,
        __nv_bfloat16* __restrict__ out) {
    extern __shared__ __align__(1024) uint8_t smem_raw[];
    const uint32_t sb = smem_u32(smem_raw);
    if ((sb & 0xFFFFFFu) != SB0) __trap();
    const uint32_t bars = sb + OFF_BAR;
    float* s_misc = reinterpret_cast<float*>(smem_raw + OFF_BAR + B_MISC);
    const int bid = blockIdx.x;
    const int h = bid >> 2, qb = bid & 3;

    {
        const int warp = __shfl_sync(0xffffffffu, threadIdx.x >> 5, 0), lane = threadIdx.x & 31;
        const int mt = p1_mp(bid) * 2 + (bid & 1), nt = p1_nt(bid);
        if (warp >= 12 && warp < 14) {
            if (lane < 15) asm volatile("prefetch.global.L2 [%0];" ::"l"(wb + (warp - 12) * 245760 + bid * 1920 + lane * 128) : "memory");
            if (lane >= 16) asm volatile("prefetch.global.L2 [%0];" ::"l"(x + (size_t)(bid * 16 + lane - 16) * DM + (warp - 12) * 64) : "memory");
        }
        if (threadIdx.x == 352) {
            prefetch_tmap(&tmX);
#pragma unroll
            for (int i = 0; i < 6; i++) mbar_init(bars + B_FULL + 8 * i, 1);
            fence_mbar_init();
        } else if (threadIdx.x == 256) {
            prefetch_tmap(&tmWb);
        } else if (threadIdx.x == 32) {
#pragma unroll
            for (int i = 0; i < 6; i++) mbar_init(bars + B_EMPTY + 8 * i, 16);
#pragma unroll
            for (int i = 0; i < 4; i++) mbar_init(bars + B_PUB + 8 * i, 4);
            fence_mbar_init();
        } else if (threadIdx.x == 64) {
            mbar_init(bars + B_STGB, 8); mbar_init(bars + B_STGA, 8);
            mbar_init(bars + B_RET, 16); mbar_init(bars + B_RET + 8, 8); mbar_init(bars + B_RET + 16, 16); mbar_init(bars + B_RET + 24, 16);
            mbar_init(bars + B_LD, 16); mbar_init(bars + B_NRM, 4); mbar_init(bars + B_HLP, 4);
            fence_mbar_init();
        } else if (threadIdx.x == 128) {
#pragma unroll
            for (int i = 0; i < 10; i++) mbar_init(bars + B_XCH + 8 * i, 1);
            fence_mbar_init();
#pragma unroll
            for (int i = 0; i < 2; i++) {
                mbar_expect_tx(bars + B_XCH + 8 * i, 10240);
                mbar_expect_tx(bars + B_AF + 32 * i + 8, 16384); mbar_expect_tx(bars + B_AF + 32 * i + 16, 24576);
            }
        } else if (threadIdx.x == 160) {
            mbar_init(bars + B_AE, 8); mbar_init(bars + B_R26, 16); mbar_init(bars + B_W0, 8); mbar_init(bars + B_W0 + 8, 8); mbar_init(bars + B_W0 + 16, 8);
            fence_mbar_init();
        } else if (threadIdx.x == 96) {
#pragma unroll
            for (int i = 0; i < 11; i++) mbar_init(bars + B_KV + 8 * i, i == 3 ? 2 : 1);
            s_misc[-4] = 0.f; s_misc[-3] = 0.f;
            fence_mbar_init();
        }
        __syncwarp();
        cluster_arrive();
        if (warp == 11 && elect_one()) {
            tma_x(sb + OFF_X, &tmX, 0, mt * 8, bars + B_FULL);
#pragma unroll
            for (int i = 0; i < 6; i++) mbar_expect_tx(bars + B_FULL + 8 * i, (i & 1) ? 16384 : 32768);
        }
        __syncwarp();
        cluster_wait();
        const uint32_t t_start = clock_lo();
        if ((warp == 8 || warp == 10) && elect_one()) {
            const int col = (bid & 1) * 128 + (warp == 10 ? 64 : 0);
#pragma unroll
            for (int i = 0; i < 2; i++) tma_3d_mc(sb + i * 16384 + col * 64, &tmWb, col, nt, i * 32, bars + B_FULL + 8 * i, 3);
        }
        __syncwarp();

        if (warp < 8) {
            asm volatile("setmaxnreg.inc.sync.aligned.u32 152;");
            const int wg = warp >> 2, t = lane & 3;
            const uint64_t da0 = mkdesc(SB0 + OFF_X, 16, 1024, 1) + wg * 512, db0 = mkdesc(SB0, 4096, 1024, 1);
            uint32_t rel;
            asm volatile("mapa.shared::cluster.u32 %0, %1, %2;" : "=r"(rel) : "r"(bars + B_EMPTY), "r"(lane & 1));
            uint32_t xs = 0, xprev = 0, ph = 0;
#pragma unroll 1
            for (int br = 0; br < 2; br++) {
                float acc0[64], acc1[56];
                auto pair = [&](bool first) {
                    const uint64_t da = da0 + xs * 1024, db = db0 + xs * 2048;
#pragma unroll
                    for (int e = 0; e < 2; e++) {
                        mbar_wait(bars + B_FULL + 16 * xs + 8 * e, ph);
                        wg_fence();
                        if (first && e == 0) { wgmma_ss128f(acc0, da, db); wgmma_ss112f(acc1, da, db + 512); }
                        else { wgmma_ss128(acc0, da + e * 4, db + e * 1024); wgmma_ss112(acc1, da + e * 4, db + e * 1024 + 512); }
                        wgmma_ss128(acc0, da + e * 4 + 2, db + e * 1024 + 128);
                        wgmma_ss112(acc1, da + e * 4 + 2, db + e * 1024 + 640);
                        wg_commit();
                        if (!first || e) {
                            wg_wait<1>();
                            if (lane < 2) asm volatile("mbarrier.arrive.shared::cluster.b64 _, [%0];" ::"r"(e ? rel + 16 * xs : rel + 16 * xprev + 8) : "memory");
                        }
                    }
                    xprev = xs;
                    if (++xs == 3) { xs = 0; ph ^= 1; }
                };
                pair(true);
#pragma unroll 1
                for (int kp = 1; kp < 10; kp++) pair(false);
                wg_wait<0>();
                pin(acc0); pin(acc1);
                if (lane < 2) asm volatile("mbarrier.arrive.shared::cluster.b64 _, [%0];" ::"r"(rel + 16 * xprev + 8) : "memory");
                const uint32_t wst = sb + (br == 0 ? OFF_R : 0) + warp * 768 + (lane & 7) * 16;
                const uint32_t a0 = wst + (lane >> 3) * 128;
                const uint32_t a1 = wst + (lane < 16 ? 512 + (lane >> 3) * 128 : 6144 + ((lane >> 3) - 2) * 128);
                const uint32_t a2 = wst + 6144 + 256 + (lane >> 3) * 128;
                const bool poly = (POLY16 >> ((mt * 8 + warp) & 15)) & 1;
                const uint32_t augq = br ? 0u : (t & 1) ? 0x00003D2Du : 0x3F8043C0u;
                const uint32_t augk = br ? 0u : (t & 1) ? (poly ? 0u : 0x00003F80u) : (poly ? 0x00003F80u : 0x3F800000u);
                const uint32_t augv = (t & 1) ? 0u : 0x00003F80u;
                const float sc2 = br ? 0.5f * QSCALE : QSCALE;
                const int hp0 = (br ? p1_nta(nt) : nt) * 6;
#define ACC(i) ((i) < 64 ? acc0[(i) & 63] : acc1[((i) - 64) % 56])
                if (hp0 < 16) {
#pragma unroll
                    for (int i = 0; i < 80; i++) ACC(i) *= (i / 4) % 5 == 2 ? sc2 : QSCALE;
                    if (hp0 < 12) {
#pragma unroll
                        for (int i = 80; i < 120; i++) ACC(i) *= (i / 4) % 5 == 2 ? sc2 : QSCALE;
                    }
                }
                if (br == 1) named_sync(1, 256);
                else mbar_wait(bars + B_HDR, 0);
#pragma unroll
                for (int u = 0; u < 6; u++) {
                    uint32_t v[2][5];
#pragma unroll
                    for (int j = 0; j < 10; j++) { const int i = (5 * u + j % 5) * 4 + 2 * (j / 5); v[j / 5][j % 5] = pack2(ACC(i), ACC(i + 1)); }
#undef ACC
                    const uint32_t aug = hp0 + u < 16 ? augq : hp0 + u < 32 ? augk : augv;
                    stsm4(a0 + u * 12288, v[0][0], v[0][1], t < 2 ? v[0][2] : aug, v[1][0]);
                    stsm4(a1 + u * 12288, v[1][1], t < 2 ? v[1][2] : aug, v[0][3], v[0][4]);
                    stsm4(a2 + u * 12288, t < 2 ? aug : v[0][2], v[1][3], v[1][4], t < 2 ? aug : v[1][2]);
                }
                fence_async_smem();
                __syncwarp();
                if (lane == 0) mbar_arrive(bars + B_STGB + 8 * br);
            }
            asm volatile("setmaxnreg.dec.sync.aligned.u32 128;");
        } else if (warp < 12) {
            asm volatile("setmaxnreg.dec.sync.aligned.u32 80;");
            if (warp != 9) {
                if (warp == 11) {
                    uint32_t xs = 0, ph = 0;
#pragma unroll
                    for (int i = 1; i < 3; i++) {
                        while (clock_lo() - t_start < (i == 1 ? G1 : G2)) {}
                        if (elect_one()) tma_x(sb + OFF_X + i * 16384, &tmX, i * 64, mt * 8, bars + B_FULL + 16 * i);
                    }
#pragma unroll 1
                    for (int P = 3; P < 20; P++) {
                        const int k0 = (P < 10 ? P : P - 13) * 64;
                        mbar_wait(bars + B_EMPTY + 16 * xs + 8, ph);
                        if (elect_one()) {
                            if (k0 >= 0) tma_x(sb + OFF_X + xs * 16384, &tmX, k0, mt * 8, bars + B_FULL + 16 * xs);
                            if (P == 7) { prefetch_tmap(&tmWa); prefetch_tmap(&tmS); }
                        }
                        if (++xs == 3) { xs = 0; ph ^= 1; }
                    }
                } else {
                    const int col = (bid & 1) * 128 + (warp == 10 ? 64 : 0);
                    uint32_t s = 0, ph = 0;
#pragma unroll
                    for (int i = 2; i < 6; i++) {
                        while (clock_lo() - t_start < (i < 4 ? G1 : G2)) {}
                        if (elect_one()) tma_3d_mc(sb + i * 16384 + col * 64, &tmWb, col, nt, i * 32, bars + B_FULL + 8 * i, 3);
                    }
#pragma unroll 1
                    for (int it = 6; it < 40; it++) {
                        const int k0 = (it < 20 ? it : it < 26 ? it - 6 : it - 26) * 32;
                        const CUtensorMap* tw = it >= 20 ? &tmWa : &tmWb;
                        const int ct = it >= 20 ? p1_nta(nt) : nt;
                        const int bytes = ((s & 1) || (it >= 20 && it < 26)) ? 16384 : 32768;
                        mbar_wait(bars + B_EMPTY + 8 * s, ph);
                        if (elect_one()) {
                            tma_3d_mc(sb + s * 16384 + col * 64, tw, col, ct, k0, bars + B_FULL + 8 * s, 3);
                            if (warp == 8) mbar_expect_tx(bars + B_FULL + 8 * s, bytes);
                        }
                        if (++s == 6) { s = 0; ph ^= 1; }
                    }
                }
                if (warp == 8 && elect_one()) {
                    mbar_wait(bars + B_KV, 0);
                    load_kv(sb, h, 1, 4, 4, 6);
                    bulk_g2s(sb + OFF_R + 12288, g_qkv + (size_t)h * HEAD_BYTES + qb * 24576 + 12288, 12288, bars + B_KV + 8);
                    mbar_wait(bars + B_EMPTY + 24, 0);
                    load_kv(sb, h, 2, 8, 1, 12); load_kv(sb, h, 2, 9, 11, 0);
                }
            } else {
                if (elect_one()) {
                    mbar_wait(bars + B_STGB, 0);
                    uint32_t tick = clock_lo() - PACE;
#pragma unroll 1
                    for (int i = 0; i < 24; i++) {
                        while (clock_lo() - tick < PACE) {}
                        tick += PACE;
                        bulk_s2g(g_qkv + (size_t)(nt * 12 + (i >> 1)) * HEAD_BYTES + mt * 6144 + (i & 1) * 3072, sb + OFF_R + i * 3072, 3072);
                    }
                    mbar_wait(bars + B_NRM, 0);
                    bulk_s2g(g_nrm + mt * 96 + nt * 12, bars + B_MISC, 48);
                    bulk_commit();
                    bulk_wait_all();
                    flag_add_done(g_flag + (F_QKVB + nt) * 32);
                    flag_wait_head(g_flag + F_QKVB * 32, h, 128);
                    fence_async_smem();
                    load_kv(sb, h, 0, 0, 4, 6);
                    bulk_g2s(sb + OFF_R, g_qkv + (size_t)h * HEAD_BYTES + qb * 24576, 12288, bars + B_KV);
                }
                __syncwarp();
                {
                    const uint32_t w = ldcg_u32(g_nrm + (lane < 16 ? lane * 96 + 32 + h : (qb * 4 + (lane & 3)) * 96 + h));
                    const float kn = __uint_as_float(__reduce_max_sync(0xffffffffu, lane < 16 ? w : 0u));
                    if (lane >= 16 && lane < 20) s_misc[lane] = __uint_as_float(w) * kn <= SCORE_LIMIT2 ? 0.f : 1.f;
                    __syncwarp();
                    if (elect_one()) mbar_arrive(bars + B_KV + 24);
                }
            }
            __syncwarp();
            named_sync(5, 128);
            asm volatile("setmaxnreg.inc.sync.aligned.u32 128;");
        } else {
            mbar_wait(bars + B_FULL + 40, 0);
            {
                uint4 wv[7];
#pragma unroll
                for (int e = 0; e < 7; e++) {
                    const int i = threadIdx.x - 384 + e * 128, d = bid * 800 + i;
                    const int kr = d & 7, ng = (d >> 3) % 20, kg = (d / 160) % 80, part = bid >> 4;
                    const int k = (kg < 40 ? kg : kg + 40) * 8 + (part & 1) * 320 + kr;
                    const uint8_t* src = (k < 640 ? woa + k * 1280 : wob + (k - 640) * 1280) + ((part >> 1) * 20 + ng) * 16;
                    if (i < 800) wv[e] = __ldg(reinterpret_cast<const uint4*>(src));
                }
                const uint2* gw = reinterpret_cast<const uint2*>(gate_w) + lane;
                const uint2* xr = reinterpret_cast<const uint2*>(x + (size_t)(bid * 16 + (warp - 12) * 4) * DM) + lane;
                uint2 gv[5], xv[4][5];
#pragma unroll
                for (int i = 0; i < 5; i++) gv[i] = __ldg(gw + 32 * i);
#pragma unroll
                for (int i = 0; i < 20; i++) xv[i / 5][i % 5] = __ldg(xr + 32 * i);
                float a[4];
#pragma unroll
                for (int e = 0; e < 4; e++) {
                    a[e] = 0.f;
#pragma unroll
                    for (int i = 0; i < 5; i++) {
                        a[e] = fmaf(bf_lo(xv[e][i].x), bf_lo(gv[i].x), a[e]); a[e] = fmaf(bf_hi(xv[e][i].x), bf_hi(gv[i].x), a[e]);
                        a[e] = fmaf(bf_lo(xv[e][i].y), bf_lo(gv[i].y), a[e]); a[e] = fmaf(bf_hi(xv[e][i].y), bf_hi(gv[i].y), a[e]);
                    }
                }
#pragma unroll
                for (int o = 16; o; o >>= 1) {
#pragma unroll
                    for (int e = 0; e < 4; e++) a[e] += __shfl_xor_sync(0xffffffffu, a[e], o);
                }
                const float z = lane == 0 ? a[0] : lane == 1 ? a[1] : lane == 2 ? a[2] : a[3];
                if (lane < 4) asm volatile("st.shared.f32 [%0], %1;" ::"r"(sb + OFF_R + 12800 + ((lane & 1) * 8 + (warp - 12) * 2 + (lane >> 1)) * 4), "f"(__fdividef(1.f, 1.f + __expf(-z))) : "memory");
#pragma unroll
                for (int e = 0; e < 7; e++) {
                    const int i = threadIdx.x - 384 + e * 128;
                    if (i < 800) asm volatile("st.shared.v4.b32 [%0], {%1,%2,%3,%4};" ::"r"(sb + OFF_R + i * 16), "r"(wv[e].x), "r"(wv[e].y), "r"(wv[e].z), "r"(wv[e].w) : "memory");
                }
                fence_async_smem();
                __syncwarp();
                if (lane == 0) mbar_arrive(bars + B_HLP);
                if (warp == 15 && elect_one()) {
                    mbar_wait(bars + B_HLP, 0);
                    bulk_s2g(g_wo + bid * 800, sb + OFF_R, 12800);
                    bulk_s2g(g_gate + bid * 16, sb + OFF_R + 12800, 64);
                    bulk_commit();
                    bulk_wait_all();
                    mbar_arrive(bars + B_HDR);
                    flag_add_done(g_flag + F_HELP * 32);
                }
                __syncwarp();
            }
            mbar_wait(bars + B_STGB, 0);
#pragma unroll 1
            for (int hs = warp - 12; hs < 12; hs += 4) {
                uint32_t nm = 0;
                if (nt * 12 + hs < 64) {
#pragma unroll
                    for (int i = 0; i < 4; i++) {
                        const uint32_t a = sb + OFF_R + hs * 6144 + (i * 4 + (lane >> 3)) * 384 + (lane & 7) * 16;
                        const uint4 k0 = lds128(a), k1 = lds128(a + 128);
                        uint32_t k2, k3;
                        asm volatile("ld.shared.v2.b32 {%0,%1}, [%2];" : "=r"(k2), "=r"(k3) : "r"(a + 256 + (hs & 1) * 8));
                        uint32_t n0 = hfma2(k2, k2, 0u), n1 = hfma2(k3, k3, 0u);
                        n0 = hfma2(k0.x, k0.x, n0); n1 = hfma2(k0.y, k0.y, n1); n0 = hfma2(k0.z, k0.z, n0); n1 = hfma2(k0.w, k0.w, n1);
                        n0 = hfma2(k1.x, k1.x, n0); n1 = hfma2(k1.y, k1.y, n1); n0 = hfma2(k1.z, k1.z, n0); n1 = hfma2(k1.w, k1.w, n1);
                        nm = max(nm, __float_as_uint((bf_lo(n0) + bf_hi(n0)) + (bf_lo(n1) + bf_hi(n1))));
                    }
                }
                nm = __reduce_max_sync(0xffffffffu, nm);
                if (lane == 0) s_misc[hs] = __uint_as_float(nm) * 1.03f;
            }
            fence_async_smem();
            __syncwarp();
            if (lane == 0) mbar_arrive(bars + B_NRM);
        }
    }

    uint32_t aflag;
    {
        const uint64_t dK0 = mkdesc(sb, 128, 384, 0), dK1 = mkdesc(sb + 256, 0, 384, 0), dV = mkdesc(sb, 384, 128, 0);
        const int wid = fresh_wid();
        mbar_wait(bars + B_KV, 0);
#pragma unroll 1
        for (int u = 0; u < 2; u++) {
            uint32_t q[8];
            {
                const uint32_t a = sb + OFF_R + (u * 32 + here(wid) * 2) * 384 + (fresh_tid() & 31) * 4;
                q[0] = lds32(a); q[1] = lds32(a + 384); q[2] = lds32(a + 128); q[3] = lds32(a + 512);
                q[4] = lds32(a + 256); q[5] = lds32(a + 640);
                q[6] = lds32(bars + B_ZERO); q[7] = lds32(bars + B_ZERO + 4);
            }
            float o[12];
#pragma unroll
            for (int i = 0; i < 12; i++) o[i] = 0.f;
            pin(o); pin(q);
            float s0[32], s1[32];
            uint32_t p[16];
            float g0, g1;
            wg_fence(); qk_tile(s0, q, dK0 + (k_off(0) >> 4), dK1 + (k_off(0) >> 4)); wg_commit();
#pragma unroll
            for (int j = 0; j < 32; j += 2) {
                qk_tile(s1, q, dK0 + (k_off(j + 1) >> 4), dK1 + (k_off(j + 1) >> 4)); wg_commit();
                wg_wait<1>(); pin(s0);
                exp_pv_tile(s0, p, o, dV + (v_off(j) >> 4), POLY16 >> (4 * (j & 3)));
                if (j == 2 || j == 6 || j == 18) { mbar_wait(bars + B_KV + (j == 2 ? 8 : j == 6 ? 16 : 24), 0); wg_fence(); }
                const bool ahead = j + 2 < 32 && j != LJ;
                if (ahead) { qk_tile(s0, q, dK0 + (k_off(j + 2) >> 4), dK1 + (k_off(j + 2) >> 4)); wg_commit(); }
                {
                    if (j == 10) { if (u == 1 && elect_one()) mbar_arrive(bars + B_RET); }
                    if (j == 4) {
                        if (u == 0 && wid == 14 && elect_one()) {
                            const int bid = fresh_bid();
                            mbar_wait(bars + B_STGA, 0);
                            tma_store_3d(&tmS, sb, 0, (p1_mp(bid) * 2 + (bid & 1)) * 16, 96 + p1_nta(p1_nt(bid)) * 12);
                            bulk_commit();
                        }
                        __syncwarp();
                    }
                    if (j == 12) {
                        if (u == 0 && wid == 14 && elect_one()) service(sb, 0, 0);
                        __syncwarp();
                    }
                    if (j == 10) { if (u == 1 && wid == 9 && elect_one()) service(sb, 1, 0); __syncwarp(); }
                    if (j == 20 || j == 26) { if (u == 1 && elect_one()) mbar_arrive(bars + (j == 20 ? B_RET + 24 : B_R26)); }
                    if (j == 18) { if (u == 1 && wid == 5 && elect_one()) service(sb, 4, 0); __syncwarp(); }
                    if (j == 22) { if (u == 1 && wid == 14 && elect_one()) service(sb, 3, 0); __syncwarp(); }
                    if (j == 28) { if (u == 1 && wid == 10 && elect_one()) service(sb, 2, aflag); __syncwarp(); }
                    if (j == 26) {
                        const float* gp = g_gate + (uint32_t)((fresh_bid() & 3) * 512 + u * 256 + here(wid) * 16) + (((uint32_t)fresh_tid() & 31) >> 2);
                        g0 = ldcg_f32(gp); g1 = ldcg_f32(gp + 8);
                        const int b2 = fresh_bid();
                        aflag = ld_relaxed(u ? atta_in(b2) : g_flag + (F_QKVA + (uint32_t)(min(fresh_tid() & 31, 2) * 32 + (b2 >> 2)) / 12u) * 32);
                    }
                }
                if (ahead) wg_wait<1>(); else wg_wait<0>();
                pin(s1);
                exp_pv_tile(s1, p, o, dV + (v_off(j + 1) >> 4), POLY16 >> (4 * ((j + 1) & 3)));
                if (j == LJ) {
                    wg_wait<0>();
                    if (u == 1) local_attn(sb, here(wid), dK0, dK1, dV);
                    wg_fence(); qk_tile(s0, q, dK0 + (k_off(j + 2) >> 4), dK1 + (k_off(j + 2) >> 4)); wg_commit();
                }
            }
            const int tid = fresh_tid(), lane = tid & 31, warp = here(wid);
            const int bid = fresh_bid(), h = bid >> 2, qb = bid & 3;
            if (u == 0 && wid == 13) {
                if (__all_sync(0xffffffffu, aflag >= 16)) asm volatile("fence.acquire.gpu;" ::: "memory");
                else if (elect_one()) flag_wait_head(g_flag + F_QKVA * 32, h, 0);
                __syncwarp();
            }
            wg_wait<0>(); pin(o);
            if (u == 1 && lane == 0) mbar_arrive(bars + B_RET + 16);
            float l0, l1;
            uint32_t w[6];
            finish_o(o, w, h & 1, 1.f - g0, 1.f - g1, lane, l0, l1);
            store_o(w, out_ptr(qb * 32 + u * 16 + warp, h, 80, lane), 0);
            const float sum = (((o[0] + o[1]) + (o[2] + o[3])) + ((o[4] + o[5]) + (o[6] + o[7]))) + ((o[8] + o[9]) + (o[10] + o[11]));
            if (__any_sync(0xffffffffu, !(fminf(l0, l1) >= 0x1p-30f && fmaxf(l0, l1) <= 0x1p100f && fabsf(sum) <= 1e37f && s_misc[16 + u * 2 + (warp >> 3)] == 0.f)))
                exact_rows(h, qb * 32 + u * 16 + warp, lane);
        }
        __syncwarp();
        if (elect_one()) mbar_arrive(bars + B_PUB + (wid >> 2) * 8);
    }

    {
        const int tid = fresh_tid(), lane = tid & 31;
        const int warp = __shfl_sync(0xffffffffu, tid >> 5, 0);
        const int bid = fresh_bid(), rank = bid & 1;
        if (warp >= 8) {
            asm volatile("setmaxnreg.dec.sync.aligned.u32 40;");
            if ((warp == 8 || warp == 12 || warp >= 14) && elect_one()) {
                const int wg = warp == 15 ? 0 : warp == 14 ? 1 : warp >> 2;
                mbar_wait(bars + B_PUB + 8 * wg, 0);
                flag_add_done(attb_out(bid, wg));
            }
            if (warp == 13 && elect_one()) {
#pragma unroll
                for (int i = 0; i < 3; i++) { mbar_wait(bars + B_W0 + 8 * (i ? i : 1), 0); load_wo(sb, 7 + i, 1); }
            }
            if (warp == 10 && elect_one()) {
                if (aflag < 16) flag_wait(atta_in(bid), 16);
                mbar_wait(bars + B_RET + 16, 0);
                if (aflag < 16) { load_frag(sb, bid, 0, 0); load_frag(sb, bid, 1, 0); }
                mbar_wait(bars + B_W0, 0);
                load_frag(sb, bid, 0, 1);
                mbar_wait(bars + B_W0 + 8, 0);
                load_frag(sb, bid, 0, 2);
            }
            if (warp == 11 && elect_one()) {
                mbar_wait(bars + B_AE, 0);
                fence_async_smem();
                flag_wait_fast(attb_in(bid), 16);
                load_frag(sb, bid, 1, 1); load_frag(sb, bid, 1, 2);
                if (atomicAdd(g_flag + F_EXIT * 32, 1u) == 127u) {
#pragma unroll 1
                    for (int i = 0; i < F_COUNT; i++) g_flag[i * 32] = 0u;
                }
            }
        } else {
            const int mh = warp >> 2;
            const int mt64 = (bid >> 5) * 8 + mh * 4 + ((bid >> 3) & 3);
            const int pos = frag_pos(warp & 3, lane);
            const uint2* ap = g_att + (mt64 * 160 + rank * 40) * 128 + pos;
            const uint32_t as0 = sb + frag_off(mh, 0) + pos * 8, as1 = sb + frag_off(mh, 5) + pos * 8, as9 = sb + frag_off(mh, 9) + pos * 8, fb = bars + B_AF + mh * 32;
            const uint64_t db = mkdesc(SB0, 2560, 128, 0);
            uint32_t a[6][16];
            auto ldg = [&](int i) {
#pragma unroll
                for (int j = 0; j < 8; j++)
                    asm volatile("ld.global.L1::no_allocate.v2.b32 {%0, %1}, [%2];" : "=r"(a[i % 6][2 * j]), "=r"(a[i % 6][2 * j + 1])
                                 : "l"(ap + ((i / 5) * 80 + (i % 5) * 8 + j) * 128) : "memory");
            };
            auto lds = [&](int i) {
                if (i == 0 || i == 5 || i == 7) mbar_wait(fb + (i / 3) * 8, 0);
#pragma unroll
                for (int j = 0; j < 8; j++)
                    asm volatile("ld.shared.v2.b32 {%0, %1}, [%2];" : "=r"(a[i % 6][2 * j]), "=r"(a[i % 6][2 * j + 1])
                                 : "r"(i == 9 ? as9 + j * 1024 : (i < 5 ? as0 : as1) + ((i % 5) * 8 + j) * 1024) : "memory");
            };
            float snd[40], keep[40];
            const uint64_t dk = db + rank * 80, ds = db + (rank ^ 1) * 80;
            auto half = [&](float (&acc)[40], uint64_t d, int i) {
#pragma unroll
                for (int k = 0; k < 4; k++)
                    if (i + k == 0) wgmma_rs80f(acc, a[0][0], a[0][1], a[0][2], a[0][3], d + (wo_off(0) >> 4));
                    else wgmma_rs80(acc, a[i % 6][4 * k], a[i % 6][4 * k + 1], a[i % 6][4 * k + 2], a[i % 6][4 * k + 3], d + (wo_off(i) >> 4) + k * 320);
            };
            auto mma = [&](int i) {
                if (i == 0 || wo_bar(i) != wo_bar(i - 1)) mbar_wait(bars + B_WO + 8 * wo_bar(i), 0);
                pin(a[i % 6]);
                wg_fence();
                half(snd, ds, i);
                half(keep, dk, i);
                wg_commit();
            };
            lds(0); mma(0);
            wg_wait<0>();
            lds(1); mma(1);
            asm volatile("setmaxnreg.inc.sync.aligned.u32 216;");
            ldg(2); ldg(3);
            if (lane == 0) mbar_arrive(bars + B_AE);
            ldg(4);
#pragma unroll
            for (int i = 0; i < 3; i++) {
                wg_wait<1>();
                if (lane == 0) mbar_arrive(bars + B_W0 + 8 * i);
                mma(i + 2);
            }
            wg_wait<0>();
            if (lane == 0) mbar_arrive_cluster(bars + B_RET + 8, rank ^ 1);
            lds(5); lds(6);
            pin(a[5]); pin(a[0]);
            wg_fence(); half(snd, ds, 5); half(snd, ds, 6);
            half(keep, dk, 5);
            lds(7); lds(8); lds(9);
            pin(a[1]); pin(a[2]); pin(a[3]);
#pragma unroll
            for (int i = 7; i < 10; i++) { mbar_wait(bars + B_WO + 8 * wo_bar(i), 0); wg_fence(); half(snd, ds, i); }
            wg_commit();
#pragma unroll
            for (int i = 6; i < 10; i++) half(keep, dk, i);
            wg_commit();
            const uint32_t xs = sb + (mh ? wo_off(4) : wo_off(3)) + (tid & 127) * 16;
            {
                uint32_t ra, rb;
                asm volatile("mapa.shared::cluster.u32 %0, %1, %2;" : "=r"(ra) : "r"(xs), "r"(rank ^ 1));
                asm volatile("mapa.shared::cluster.u32 %0, %1, %2;" : "=r"(rb) : "r"(bars + B_XCH + 8 * mh), "r"(rank ^ 1));
                mbar_wait(bars + B_RET + 8, 0);
                wg_wait<1>();
                pin(snd);
#pragma unroll
                for (int j = 0; j < 5; j++)
                    asm volatile("st.async.weak.shared::cluster.mbarrier::complete_tx::bytes.v4.b32 [%0], {%1,%2,%3,%4}, [%5];"
                                 ::"r"(ra + j * 2048), "r"(pack2(snd[8 * j], snd[8 * j + 1])), "r"(pack2(snd[8 * j + 2], snd[8 * j + 3])),
                                   "r"(pack2(snd[8 * j + 4], snd[8 * j + 5])), "r"(pack2(snd[8 * j + 6], snd[8 * j + 7])), "r"(rb) : "memory");
            }
            named_sync(8 + mh, 128);
            mbar_wait(bars + B_XCH + 8 * mh, 0);
            uint4 rcv[10];
#pragma unroll
            for (int j = 0; j < 5; j++) {
                const uint4 v = lds128(xs + j * 2048);
                rcv[2 * j] = make_uint4(v.x << 16, v.x & 0xffff0000u, v.y << 16, v.y & 0xffff0000u);
                rcv[2 * j + 1] = make_uint4(v.z << 16, v.z & 0xffff0000u, v.w << 16, v.w & 0xffff0000u);
            }
            wg_wait<0>();
            pin(keep);
            uint32_t w[20];
#pragma unroll
            for (int j = 0; j < 10; j++) {
                const uint4 o = rcv[j];
                w[2 * j] = pack2(keep[4 * j] + __uint_as_float(o.x), keep[4 * j + 1] + __uint_as_float(o.y));
                w[2 * j + 1] = pack2(keep[4 * j + 2] + __uint_as_float(o.z), keep[4 * j + 3] + __uint_as_float(o.w));
            }
            const uint32_t ot = sb + frag_off(mh, 5) + (warp & 3) * 2816;
            const uint32_t sa = ot + (lane & 15) * 176 + (lane >> 4) * 16;
#pragma unroll
            for (int j = 0; j < 5; j++) stsm4(sa + j * 32, w[4 * j], w[4 * j + 1], w[4 * j + 2], w[4 * j + 3]);
            __syncwarp();
            __nv_bfloat16* ob = out + (size_t)(mt64 * 64 + (warp & 3) * 16) * DM + (bid & 7) * 80;
#pragma unroll
            for (int i = 0; i < 5; i++) {
                const int c = lane + 32 * i, r = c / 10;
                stg128(ob + ((r & 7) * 2 + (r >> 3)) * DM + (c % 10) * 8, lds128(ot + r * 176 + (c % 10) * 16));
            }
        }
    }
}

typedef CUresult (*EncodeFn)(CUtensorMap*, CUtensorMapDataType, cuuint32_t, void*, const cuuint64_t*, const cuuint64_t*,
                             const cuuint32_t*, const cuuint32_t*, CUtensorMapInterleave, CUtensorMapSwizzle,
                             CUtensorMapL2promotion, CUtensorMapFloatOOBfill);

void make_map(EncodeFn fn, CUtensorMap* tm, const void* ptr, int rank, const cuuint64_t* dims, const cuuint64_t* strides,
              const cuuint32_t* box, CUtensorMapSwizzle swz) {
    const cuuint32_t es[4] = {1, 1, 1, 1};
    fn(tm, CU_TENSOR_MAP_DATA_TYPE_BFLOAT16, rank, const_cast<void*>(ptr), dims, strides, box, es, CU_TENSOR_MAP_INTERLEAVE_NONE,
       swz, CU_TENSOR_MAP_L2_PROMOTION_L2_256B, CU_TENSOR_MAP_FLOAT_OOB_FILL_NONE);
}

}

extern "C" void kernel_launch(void* const* d_in, const int* in_sizes, int n_in, void* d_out, int out_size) {
    (void)in_sizes; (void)n_in; (void)out_size;
    const __nv_bfloat16* x = (const __nv_bfloat16*)d_in[0];
    const __nv_bfloat16* wqkv_a = (const __nv_bfloat16*)d_in[1];
    const __nv_bfloat16* wo_a = (const __nv_bfloat16*)d_in[2];
    const __nv_bfloat16* wqkv_b = (const __nv_bfloat16*)d_in[4];
    const __nv_bfloat16* wo_b = (const __nv_bfloat16*)d_in[5];
    const __nv_bfloat16* gate_w = (const __nv_bfloat16*)d_in[6];

    void* fnp = nullptr;
    cudaDriverEntryPointQueryResult qr;
    cudaGetDriverEntryPoint("cuTensorMapEncodeTiled", &fnp, cudaEnableDefault, &qr);
    EncodeFn enc = (EncodeFn)fnp;
    void* qkv = nullptr;
    cudaGetSymbolAddress(&qkv, g_qkv);

    CUtensorMap tmX, tmWb, tmWa, tmS;
    {
        const cuuint64_t d[4] = {640, 8, 2, 128}, s[3] = {2560, 1280, 20480};
        const cuuint32_t b[4] = {64, 8, 2, 8};
        make_map(enc, &tmX, x, 4, d, s, b, CU_TENSOR_MAP_SWIZZLE_128B);
    }
    {
        const cuuint64_t d[3] = {240, 8, 640}, s[2] = {480, 3840};
        const cuuint32_t b[3] = {64, 1, 32};
        make_map(enc, &tmWb, wqkv_b, 3, d, s, b, CU_TENSOR_MAP_SWIZZLE_128B);
        make_map(enc, &tmWa, wqkv_a, 3, d, s, b, CU_TENSOR_MAP_SWIZZLE_128B);
    }
    {
        const cuuint64_t d[3] = {192, 256, 192}, s[2] = {384, (cuuint64_t)HEAD_BYTES};
        const cuuint32_t b[3] = {192, 16, 12};
        make_map(enc, &tmS, qkv, 3, d, s, b, CU_TENSOR_MAP_SWIZZLE_NONE);
    }
    cudaFuncSetAttribute(k_fused, cudaFuncAttributeMaxDynamicSharedMemorySize, SMEM_BYTES);
    k_fused<<<128, 512, SMEM_BYTES, cudaStreamPerThread>>>(tmX, tmWb, tmWa, tmS, x, gate_w, (const uint8_t*)wqkv_b,
                                                          (const uint8_t*)wo_a, (const uint8_t*)wo_b, (__nv_bfloat16*)d_out);
}
```

```cpp
#include <cuda_runtime.h>
#include <cuda_bf16.h>
#include <cuda.h>
#include <stdint.h>

namespace {

constexpr int SEQ = 2048, DM = 640;
constexpr int HEAD_BYTES = 256 * 384;
constexpr uint32_t POLY16 = 0xddddu;
constexpr float QSCALE = 0.22360679774997896f * 1.4426950408889634f;

__device__ __align__(1024) uint8_t g_qkv[2 * 96 * HEAD_BYTES];
__device__ __align__(128) float g_gate[SEQ];
__device__ __align__(128) float g_nrm[16 * 96];
enum { F_QKVB = 0, F_QKVA = 8, F_HELP = 16, F_EXIT = 17, F_ATTA = 18, F_ATTB = 26, F_COUNT = 58 };
__device__ uint32_t g_flag[F_COUNT * 32];
__device__ __align__(1024) uint4 g_wo[8 * 160 * 10 * 8];
__device__ __align__(1024) uint2 g_att[32 * 160 * 128];

__device__ __forceinline__ uint32_t slot_tile(uint32_t hs) { return (hs & 15) < 12 ? hs >> 4 : hs < 48 ? 6 : 7; }
__device__ __forceinline__ uint32_t slot_index(uint32_t hs) { return (hs & 15) < 12 ? (hs >> 4) * 12 + (hs & 15) : 72 + (hs >> 4) * 4 + (hs & 3); }
__device__ __forceinline__ uint32_t tile_slot(uint32_t t, uint32_t i) { return t < 6 ? t * 16 + i : ((t - 6) * 3 + (i >> 2)) * 16 + 12 + (i & 3); }

__device__ __forceinline__ uint32_t smem_u32(const void* p) { return (uint32_t)__cvta_generic_to_shared(p); }
__device__ __forceinline__ void mbar_init(uint32_t bar, int cnt) { asm volatile("mbarrier.init.shared::cta.b64 [%0], %1;" ::"r"(bar), "r"(cnt) : "memory"); }
__device__ __forceinline__ void mbar_expect_tx(uint32_t bar, int bytes) { asm volatile("mbarrier.arrive.expect_tx.shared::cta.b64 _, [%0], %1;" ::"r"(bar), "r"(bytes) : "memory"); }
__device__ __forceinline__ void mbar_arrive(uint32_t bar) { asm volatile("mbarrier.arrive.shared::cta.b64 _, [%0];" ::"r"(bar) : "memory"); }
__device__ __forceinline__ bool mbar_try(uint32_t bar, uint32_t parity) {
    uint32_t ok;
    asm volatile("{\n.reg .pred p;\nmbarrier.try_wait.parity.shared::cta.b64 p, [%1], %2;\nselp.u32 %0, 1, 0, p;\n}\n" : "=r"(ok) : "r"(bar), "r"(parity) : "memory");
    return ok;
}
__device__ __forceinline__ void mbar_wait(uint32_t bar, uint32_t parity) {
    if (mbar_try(bar, parity)) return;
#pragma unroll 1
    for (int i = 0; i < (1 << 21); i++)
        if (mbar_try(bar, parity)) return;
    __trap();
}
__device__ __forceinline__ void fence_mbar_init() { asm volatile("fence.mbarrier_init.release.cluster;" ::: "memory"); }
__device__ __forceinline__ void tma_x(uint32_t dst, const CUtensorMap* tm, int k, int blk16, uint32_t bar) {
    asm volatile("cp.async.bulk.tensor.4d.shared::cluster.global.mbarrier::complete_tx::bytes [%0], [%1, {%2, %5, %5, %3}], [%4];"
                 ::"r"(dst), "l"(tm), "r"(k), "r"(blk16), "r"(bar), "r"(0) : "memory");
}
__device__ __forceinline__ void tma_3d_mc(uint32_t dst, const CUtensorMap* tm, int c0, int c1, int c2, uint32_t bar, uint16_t mask) {
    asm volatile("cp.async.bulk.tensor.3d.shared::cluster.global.mbarrier::complete_tx::bytes.multicast::cluster [%0], [%1, {%2, %3, %4}], [%5], %6;"
                 ::"r"(dst), "l"(tm), "r"(c0), "r"(c1), "r"(c2), "r"(bar), "h"(mask) : "memory");
}
__device__ __forceinline__ void mbar_arrive_cluster(uint32_t bar, uint32_t cta) {
    asm volatile("{\n.reg .b32 ra;\nmapa.shared::cluster.u32 ra, %0, %1;\nmbarrier.arrive.shared::cluster.b64 _, [ra];\n}\n" ::"r"(bar), "r"(cta) : "memory");
}
__device__ __forceinline__ void tma_store_3d(const CUtensorMap* tm, uint32_t src, int c0, int c1, int c2) {
    asm volatile("cp.async.bulk.tensor.3d.global.shared::cta.bulk_group [%0, {%2, %3, %4}], [%1];" ::"l"(tm), "r"(src), "r"(c0), "r"(c1), "r"(c2) : "memory");
}
__device__ __forceinline__ void cluster_arrive() { asm volatile("barrier.cluster.arrive.relaxed.aligned;" ::: "memory"); }
__device__ __forceinline__ void cluster_wait() { asm volatile("barrier.cluster.wait.aligned;" ::: "memory"); }
__device__ __forceinline__ void named_sync(int id, int n) { asm volatile("bar.sync %0, %1;" ::"r"(id), "r"(n) : "memory"); }
__device__ __forceinline__ void flag_add_done(uint32_t* p) {
    asm volatile("fence.proxy.async.global;\nred.release.gpu.global.add.u32 [%0], 1;" ::"l"(p) : "memory");
}
__device__ __forceinline__ void flag_wait(const uint32_t* p, uint32_t target) {
#pragma unroll 1
    for (int i = 0; i < (1 << 22); i++) {
        uint32_t v;
        asm volatile("ld.acquire.gpu.global.u32 %0, [%1];" : "=r"(v) : "l"(p) : "memory");
        if (v >= target) return;
        __nanosleep(20);
    }
    __trap();
}
__device__ __forceinline__ void flag_wait_fast(const uint32_t* p, uint32_t target) {
    uint32_t v0, v1, v2;
    asm volatile("ld.relaxed.gpu.global.u32 %0, [%1];" : "=r"(v0) : "l"(p) : "memory");
    __nanosleep(100);
    asm volatile("ld.relaxed.gpu.global.u32 %0, [%1];" : "=r"(v1) : "l"(p) : "memory");
    __nanosleep(100);
#pragma unroll 1
    for (int i = 0; i < (1 << 22); i++) {
        asm volatile("ld.relaxed.gpu.global.u32 %0, [%1];" : "=r"(v2) : "l"(p) : "memory");
        if (v0 >= target) break;
        asm volatile("ld.relaxed.gpu.global.u32 %0, [%1];" : "=r"(v0) : "l"(p) : "memory");
        if (v1 >= target) break;
        asm volatile("ld.relaxed.gpu.global.u32 %0, [%1];" : "=r"(v1) : "l"(p) : "memory");
        if (v2 >= target) break;
        if (i == (1 << 22) - 1) __trap();
    }
    asm volatile("fence.acquire.gpu;" ::: "memory");
}
__device__ __forceinline__ void flag_wait_head(const uint32_t* base, int h, uint32_t help_target) {
    const uint32_t *p0 = base + slot_tile(h) * 32, *p1 = base + slot_tile(32 + h) * 32, *p2 = base + slot_tile(64 + h) * 32;
    const uint32_t target = 16;
#pragma unroll 1
    for (int i = 0; i < (1 << 22); i++) {
        uint32_t v0, v1, v2, v3;
        asm volatile("ld.relaxed.gpu.global.u32 %0, [%1];" : "=r"(v3) : "l"(g_flag + F_HELP * 32) : "memory");
        asm volatile("ld.relaxed.gpu.global.u32 %0, [%1];" : "=r"(v0) : "l"(p0) : "memory");
        asm volatile("ld.relaxed.gpu.global.u32 %0, [%1];" : "=r"(v1) : "l"(p1) : "memory");
        asm volatile("ld.relaxed.gpu.global.u32 %0, [%1];" : "=r"(v2) : "l"(p2) : "memory");
        if (v0 >= target && v1 >= target && v2 >= target && v3 >= help_target) { asm volatile("fence.acquire.gpu;" ::: "memory"); return; }
        __nanosleep(40);
    }
    __trap();
}
__device__ __forceinline__ uint32_t ld_relaxed(const uint32_t* p) { uint32_t v; asm volatile("ld.relaxed.gpu.global.u32 %0, [%1];" : "=r"(v) : "l"(p) : "memory"); return v; }
__device__ __forceinline__ float ldcg_f32(const float* p) { float v; asm volatile("ld.global.cg.f32 %0, [%1];" : "=f"(v) : "l"(p) : "memory"); return v; }
__device__ __forceinline__ uint32_t ldcg_u32(const void* p) { uint32_t v; asm volatile("ld.global.cg.b32 %0, [%1];" : "=r"(v) : "l"(p) : "memory"); return v; }
__device__ __forceinline__ void bulk_g2s(uint32_t dst, const void* src, int bytes, uint32_t bar) {
    asm volatile("fence.proxy.async.global;\ncp.async.bulk.shared::cluster.global.mbarrier::complete_tx::bytes [%0], [%1], %2, [%3];"
                 ::"r"(dst), "l"(src), "r"(bytes), "r"(bar) : "memory");
}
__device__ __forceinline__ void bulk_s2g(void* dst, uint32_t src, int bytes) {
    asm volatile("cp.async.bulk.global.shared::cta.bulk_group [%0], [%1], %2;" ::"l"(dst), "r"(src), "r"(bytes) : "memory");
}
__device__ __forceinline__ void bulk_commit() { asm volatile("cp.async.bulk.commit_group;" ::: "memory"); }
__device__ __forceinline__ void bulk_wait_all() { asm volatile("cp.async.bulk.wait_group 0;" ::: "memory"); }
__device__ __forceinline__ void fence_async_smem() { asm volatile("fence.proxy.async.shared::cta;" ::: "memory"); }
__device__ __forceinline__ void stsm4(uint32_t a, uint32_t r0, uint32_t r1, uint32_t r2, uint32_t r3) {
    asm volatile("stmatrix.sync.aligned.m8n8.x4.shared.b16 [%0], {%1,%2,%3,%4};" ::"r"(a), "r"(r0), "r"(r1), "r"(r2), "r"(r3) : "memory");
}
__device__ __forceinline__ void prefetch_tmap(const CUtensorMap* tm) { asm volatile("prefetch.tensormap [%0];" ::"l"(tm) : "memory"); }
__device__ __forceinline__ void wg_fence() { asm volatile("wgmma.fence.sync.aligned;" ::: "memory"); }
__device__ __forceinline__ void wg_commit() { asm volatile("wgmma.commit_group.sync.aligned;" ::: "memory"); }
template <int N> __device__ __forceinline__ void wg_wait() { asm volatile("wgmma.wait_group.sync.aligned %0;" ::"n"(N) : "memory"); }
__host__ __device__ constexpr uint64_t mkdesc(uint32_t addr, uint32_t lbo, uint32_t sbo, uint32_t swz) {
    return (uint64_t)((addr & 0x3FFFF) >> 4) | ((uint64_t)(lbo >> 4) << 16) | ((uint64_t)(sbo >> 4) << 32) | ((uint64_t)swz << 62);
}
template <int N> __device__ __forceinline__ void pin(float (&r)[N]) {
#pragma unroll
    for (int i = 0; i < N; i++) asm volatile("" : "+f"(r[i])::"memory");
}
template <int N> __device__ __forceinline__ void pin(uint32_t (&r)[N]) {
#pragma unroll
    for (int i = 0; i < N; i++) asm volatile("" : "+r"(r[i])::"memory");
}
__device__ __forceinline__ float ex2(float x) { float y; asm("ex2.approx.ftz.f32 %0, %1;" : "=f"(y) : "f"(x)); return y; }
__device__ __forceinline__ uint32_t pack2(float lo, float hi) { uint32_t r; asm("cvt.rn.bf16x2.f32 %0, %1, %2;" : "=r"(r) : "f"(hi), "f"(lo)); return r; }
__device__ __forceinline__ uint32_t hfma2(uint32_t a, uint32_t b, uint32_t c) { uint32_t d; asm("fma.rn.bf16x2 %0, %1, %2, %3;" : "=r"(d) : "r"(a), "r"(b), "r"(c)); return d; }
__device__ __forceinline__ float bf_lo(uint32_t v) { return __uint_as_float(v << 16); }
__device__ __forceinline__ float bf_hi(uint32_t v) { return __uint_as_float(v & 0xffff0000u); }
__device__ __forceinline__ void mma16816(float (&c)[4], uint32_t a0, uint32_t a1, uint32_t a2, uint32_t a3, uint32_t b0, uint32_t b1) {
    asm volatile("mma.sync.aligned.m16n8k16.row.col.f32.bf16.bf16.f32 {%0,%1,%2,%3}, {%4,%5,%6,%7}, {%8,%9}, {%0,%1,%2,%3};"
                 : "+f"(c[0]), "+f"(c[1]), "+f"(c[2]), "+f"(c[3]) : "r"(a0), "r"(a1), "r"(a2), "r"(a3), "r"(b0), "r"(b1));
}
__device__ __forceinline__ void mma1688(float (&c)[4], uint32_t a0, uint32_t a1, uint32_t b0) {
    asm volatile("mma.sync.aligned.m16n8k8.row.col.f32.bf16.bf16.f32 {%0,%1,%2,%3}, {%4,%5}, {%6}, {%0,%1,%2,%3};"
                 : "+f"(c[0]), "+f"(c[1]), "+f"(c[2]), "+f"(c[3]) : "r"(a0), "r"(a1), "r"(b0));
}
__device__ __forceinline__ uint32_t movm_t(uint32_t a) { uint32_t d; asm volatile("movmatrix.sync.aligned.m8n8.trans.b16 %0, %1;" : "=r"(d) : "r"(a)); return d; }
__device__ __forceinline__ void stg128(void* p, uint4 v) { asm volatile("st.global.v4.b32 [%0], {%1,%2,%3,%4};" ::"l"(p), "r"(v.x), "r"(v.y), "r"(v.z), "r"(v.w) : "memory"); }
__device__ __forceinline__ void stg64(void* p, uint32_t a, uint32_t b) { asm volatile("st.global.v2.b32 [%0], {%1,%2};" ::"l"(p), "r"(a), "r"(b) : "memory"); }
__device__ __forceinline__ int frag_pos(int warp4, int lane) { return ((lane & 2) << 5) | (warp4 << 4) | ((lane >> 2) << 1) | (lane & 1); }
__device__ __forceinline__ bool elect_one() {
    uint32_t p;
    asm volatile("{\n.reg .pred p;\nelect.sync _|p, 0xffffffff;\nselp.u32 %0, 1, 0, p;\n}\n" : "=r"(p));
    return p;
}
__device__ __forceinline__ uint32_t clock_lo() { uint32_t v; asm volatile("mov.u32 %0, %%clock;" : "=r"(v)); return v; }
__device__ __forceinline__ int fresh_bid() { int v; asm volatile("mov.u32 %0, %%ctaid.x;" : "=r"(v)); return v; }
__device__ __forceinline__ int fresh_wid() { int v; asm volatile("mov.u32 %0, %%tid.x;" : "=r"(v)); return __shfl_sync(0xffffffffu, v >> 5, 0); }
__device__ __forceinline__ int here(int v) { asm volatile("" : "+r"(v)); return v; }
__device__ __forceinline__ int fresh_tid() { int v; asm volatile("mov.u32 %0, %%tid.x;" : "=r"(v)); return v; }
__device__ __forceinline__ uint32_t lds32(uint32_t a) { uint32_t v; asm volatile("ld.shared.b32 %0, [%1];" : "=r"(v) : "r"(a) : "memory"); return v; }
__device__ __forceinline__ uint4 lds128(uint32_t a) { uint4 v; asm volatile("ld.shared.v4.b32 {%0,%1,%2,%3}, [%4];" : "=r"(v.x), "=r"(v.y), "=r"(v.z), "=r"(v.w) : "r"(a)); return v; }

__device__ __forceinline__ void wgmma_ss(float (&d)[96], uint64_t da, uint64_t db) {
    asm volatile("{\n.reg .pred p;\nsetp.eq.b32 p, 0, 0;\n"
        "wgmma.mma_async.sync.aligned.m64n192k16.f32.bf16.bf16 "
        "{%0,%1,%2,%3,%4,%5,%6,%7,%8,%9,%10,%11,%12,%13,%14,%15,%16,%17,%18,%19,"
        "%20,%21,%22,%23,%24,%25,%26,%27,%28,%29,%30,%31,%32,%33,%34,%35,%36,%37,%38,%39,"
        "%40,%41,%42,%43,%44,%45,%46,%47,%48,%49,%50,%51,%52,%53,%54,%55,%56,%57,%58,%59,"
        "%60,%61,%62,%63,%64,%65,%66,%67,%68,%69,%70,%71,%72,%73,%74,%75,%76,%77,%78,%79,"
        "%80,%81,%82,%83,%84,%85,%86,%87,%88,%89,%90,%91,%92,%93,%94,%95}, "
        "%96, %97, p, 1, 1, 0, 1;\n}\n"
        : "+f"(d[0]), "+f"(d[1]), "+f"(d[2]), "+f"(d[3]), "+f"(d[4]), "+f"(d[5]), "+f"(d[6]), "+f"(d[7]), "+f"(d[8]), "+f"(d[9]),
          "+f"(d[10]), "+f"(d[11]), "+f"(d[12]), "+f"(d[13]), "+f"(d[14]), "+f"(d[15]), "+f"(d[16]), "+f"(d[17]), "+f"(d[18]), "+f"(d[19]),
          "+f"(d[20]), "+f"(d[21]), "+f"(d[22]), "+f"(d[23]), "+f"(d[24]), "+f"(d[25]), "+f"(d[26]), "+f"(d[27]), "+f"(d[28]), "+f"(d[29]),
          "+f"(d[30]), "+f"(d[31]), "+f"(d[32]), "+f"(d[33]), "+f"(d[34]), "+f"(d[35]), "+f"(d[36]), "+f"(d[37]), "+f"(d[38]), "+f"(d[39]),
          "+f"(d[40]), "+f"(d[41]), "+f"(d[42]), "+f"(d[43]), "+f"(d[44]), "+f"(d[45]), "+f"(d[46]), "+f"(d[47]), "+f"(d[48]), "+f"(d[49]),
          "+f"(d[50]), "+f"(d[51]), "+f"(d[52]), "+f"(d[53]), "+f"(d[54]), "+f"(d[55]), "+f"(d[56]), "+f"(d[57]), "+f"(d[58]), "+f"(d[59]),
          "+f"(d[60]), "+f"(d[61]), "+f"(d[62]), "+f"(d[63]), "+f"(d[64]), "+f"(d[65]), "+f"(d[66]), "+f"(d[67]), "+f"(d[68]), "+f"(d[69]),
          "+f"(d[70]), "+f"(d[71]), "+f"(d[72]), "+f"(d[73]), "+f"(d[74]), "+f"(d[75]), "+f"(d[76]), "+f"(d[77]), "+f"(d[78]), "+f"(d[79]),
          "+f"(d[80]), "+f"(d[81]), "+f"(d[82]), "+f"(d[83]), "+f"(d[84]), "+f"(d[85]), "+f"(d[86]), "+f"(d[87]), "+f"(d[88]), "+f"(d[89]),
          "+f"(d[90]), "+f"(d[91]), "+f"(d[92]), "+f"(d[93]), "+f"(d[94]), "+f"(d[95])
        : "l"(da), "l"(db));
}
__device__ __forceinline__ void wgmma_ss(float (&d)[64], uint64_t da, uint64_t db) {
    asm volatile("{\n.reg .pred p;\nsetp.eq.b32 p, 0, 0;\n"
        "wgmma.mma_async.sync.aligned.m64n128k16.f32.bf16.bf16 "
        "{%0,%1,%2,%3,%4,%5,%6,%7,%8,%9,%10,%11,%12,%13,%14,%15,%16,%17,%18,%19,"
        "%20,%21,%22,%23,%24,%25,%26,%27,%28,%29,%30,%31,%32,%33,%34,%35,%36,%37,%38,%39,"
        "%40,%41,%42,%43,%44,%45,%46,%47,%48,%49,%50,%51,%52,%53,%54,%55,%56,%57,%58,%59,"
        "%60,%61,%62,%63}, "
        "%64, %65, p, 1, 1, 0, 1;\n}\n"
        : "+f"(d[0]), "+f"(d[1]), "+f"(d[2]), "+f"(d[3]), "+f"(d[4]), "+f"(d[5]), "+f"(d[6]), "+f"(d[7]), "+f"(d[8]), "+f"(d[9]),
          "+f"(d[10]), "+f"(d[11]), "+f"(d[12]), "+f"(d[13]), "+f"(d[14]), "+f"(d[15]), "+f"(d[16]), "+f"(d[17]), "+f"(d[18]), "+f"(d[19]),
          "+f"(d[20]), "+f"(d[21]), "+f"(d[22]), "+f"(d[23]), "+f"(d[24]), "+f"(d[25]), "+f"(d[26]), "+f"(d[27]), "+f"(d[28]), "+f"(d[29]),
          "+f"(d[30]), "+f"(d[31]), "+f"(d[32]), "+f"(d[33]), "+f"(d[34]), "+f"(d[35]), "+f"(d[36]), "+f"(d[37]), "+f"(d[38]), "+f"(d[39]),
          "+f"(d[40]), "+f"(d[41]), "+f"(d[42]), "+f"(d[43]), "+f"(d[44]), "+f"(d[45]), "+f"(d[46]), "+f"(d[47]), "+f"(d[48]), "+f"(d[49]),
          "+f"(d[50]), "+f"(d[51]), "+f"(d[52]), "+f"(d[53]), "+f"(d[54]), "+f"(d[55]), "+f"(d[56]), "+f"(d[57]), "+f"(d[58]), "+f"(d[59]),
          "+f"(d[60]), "+f"(d[61]), "+f"(d[62]), "+f"(d[63])
        : "l"(da), "l"(db));
}
__device__ __forceinline__ void wgmma_ss(float (&d)[56], uint64_t da, uint64_t db) {
    asm volatile("{\n.reg .pred p;\nsetp.eq.b32 p, 0, 0;\n"
        "wgmma.mma_async.sync.aligned.m64n112k16.f32.bf16.bf16 "
        "{%0,%1,%2,%3,%4,%5,%6,%7,%8,%9,%10,%11,%12,%13,%14,%15,%16,%17,%18,%19,"
        "%20,%21,%22,%23,%24,%25,%26,%27,%28,%29,%30,%31,%32,%33,%34,%35,%36,%37,%38,%39,"
        "%40,%41,%42,%43,%44,%45,%46,%47,%48,%49,%50,%51,%52,%53,%54,%55}, "
        "%56, %57, p, 1, 1, 0, 1;\n}\n"
        : "+f"(d[0]), "+f"(d[1]), "+f"(d[2]), "+f"(d[3]), "+f"(d[4]), "+f"(d[5]), "+f"(d[6]), "+f"(d[7]), "+f"(d[8]), "+f"(d[9]),
          "+f"(d[10]), "+f"(d[11]), "+f"(d[12]), "+f"(d[13]), "+f"(d[14]), "+f"(d[15]), "+f"(d[16]), "+f"(d[17]), "+f"(d[18]), "+f"(d[19]),
          "+f"(d[20]), "+f"(d[21]), "+f"(d[22]), "+f"(d[23]), "+f"(d[24]), "+f"(d[25]), "+f"(d[26]), "+f"(d[27]), "+f"(d[28]), "+f"(d[29]),
          "+f"(d[30]), "+f"(d[31]), "+f"(d[32]), "+f"(d[33]), "+f"(d[34]), "+f"(d[35]), "+f"(d[36]), "+f"(d[37]), "+f"(d[38]), "+f"(d[39]),
          "+f"(d[40]), "+f"(d[41]), "+f"(d[42]), "+f"(d[43]), "+f"(d[44]), "+f"(d[45]), "+f"(d[46]), "+f"(d[47]), "+f"(d[48]), "+f"(d[49]),
          "+f"(d[50]), "+f"(d[51]), "+f"(d[52]), "+f"(d[53]), "+f"(d[54]), "+f"(d[55])
        : "l"(da), "l"(db));
}
__device__ __forceinline__ void wgmma_ss(float (&d)[24], uint64_t da, uint64_t db) {
    asm volatile("{\n.reg .pred p;\nsetp.eq.b32 p, 0, 0;\n"
        "wgmma.mma_async.sync.aligned.m64n48k16.f32.bf16.bf16 "
        "{%0,%1,%2,%3,%4,%5,%6,%7,%8,%9,%10,%11,%12,%13,%14,%15,%16,%17,%18,%19,"
        "%20,%21,%22,%23}, "
        "%24, %25, p, 1, 1, 0, 1;\n}\n"
        : "+f"(d[0]), "+f"(d[1]), "+f"(d[2]), "+f"(d[3]), "+f"(d[4]), "+f"(d[5]), "+f"(d[6]), "+f"(d[7]), "+f"(d[8]), "+f"(d[9]),
          "+f"(d[10]), "+f"(d[11]), "+f"(d[12]), "+f"(d[13]), "+f"(d[14]), "+f"(d[15]), "+f"(d[16]), "+f"(d[17]), "+f"(d[18]), "+f"(d[19]),
          "+f"(d[20]), "+f"(d[21]), "+f"(d[22]), "+f"(d[23])
        : "l"(da), "l"(db));
}
__device__ __forceinline__ void wgmma_ssf(float (&d)[96], uint64_t da, uint64_t db) {
    asm volatile("{\n.reg .pred p;\nsetp.ne.b32 p, 0, 0;\n"
        "wgmma.mma_async.sync.aligned.m64n192k16.f32.bf16.bf16 "
        "{%0,%1,%2,%3,%4,%5,%6,%7,%8,%9,%10,%11,%12,%13,%14,%15,%16,%17,%18,%19,"
        "%20,%21,%22,%23,%24,%25,%26,%27,%28,%29,%30,%31,%32,%33,%34,%35,%36,%37,%38,%39,"
        "%40,%41,%42,%43,%44,%45,%46,%47,%48,%49,%50,%51,%52,%53,%54,%55,%56,%57,%58,%59,"
        "%60,%61,%62,%63,%64,%65,%66,%67,%68,%69,%70,%71,%72,%73,%74,%75,%76,%77,%78,%79,"
        "%80,%81,%82,%83,%84,%85,%86,%87,%88,%89,%90,%91,%92,%93,%94,%95}, "
        "%96, %97, p, 1, 1, 0, 1;\n}\n"
        : "=f"(d[0]), "=f"(d[1]), "=f"(d[2]), "=f"(d[3]), "=f"(d[4]), "=f"(d[5]), "=f"(d[6]), "=f"(d[7]), "=f"(d[8]), "=f"(d[9]),
          "=f"(d[10]), "=f"(d[11]), "=f"(d[12]), "=f"(d[13]), "=f"(d[14]), "=f"(d[15]), "=f"(d[16]), "=f"(d[17]), "=f"(d[18]), "=f"(d[19]),
          "=f"(d[20]), "=f"(d[21]), "=f"(d[22]), "=f"(d[23]), "=f"(d[24]), "=f"(d[25]), "=f"(d[26]), "=f"(d[27]), "=f"(d[28]), "=f"(d[29]),
          "=f"(d[30]), "=f"(d[31]), "=f"(d[32]), "=f"(d[33]), "=f"(d[34]), "=f"(d[35]), "=f"(d[36]), "=f"(d[37]), "=f"(d[38]), "=f"(d[39]),
          "=f"(d[40]), "=f"(d[41]), "=f"(d[42]), "=f"(d[43]), "=f"(d[44]), "=f"(d[45]), "=f"(d[46]), "=f"(d[47]), "=f"(d[48]), "=f"(d[49]),
          "=f"(d[50]), "=f"(d[51]), "=f"(d[52]), "=f"(d[53]), "=f"(d[54]), "=f"(d[55]), "=f"(d[56]), "=f"(d[57]), "=f"(d[58]), "=f"(d[59]),
          "=f"(d[60]), "=f"(d[61]), "=f"(d[62]), "=f"(d[63]), "=f"(d[64]), "=f"(d[65]), "=f"(d[66]), "=f"(d[67]), "=f"(d[68]), "=f"(d[69]),
          "=f"(d[70]), "=f"(d[71]), "=f"(d[72]), "=f"(d[73]), "=f"(d[74]), "=f"(d[75]), "=f"(d[76]), "=f"(d[77]), "=f"(d[78]), "=f"(d[79]),
          "=f"(d[80]), "=f"(d[81]), "=f"(d[82]), "=f"(d[83]), "=f"(d[84]), "=f"(d[85]), "=f"(d[86]), "=f"(d[87]), "=f"(d[88]), "=f"(d[89]),
          "=f"(d[90]), "=f"(d[91]), "=f"(d[92]), "=f"(d[93]), "=f"(d[94]), "=f"(d[95])
        : "l"(da), "l"(db));
}
__device__ __forceinline__ void wgmma_ssf(float (&d)[64], uint64_t da, uint64_t db) {
    asm volatile("{\n.reg .pred p;\nsetp.ne.b32 p, 0, 0;\n"
        "wgmma.mma_async.sync.aligned.m64n128k16.f32.bf16.bf16 "
        "{%0,%1,%2,%3,%4,%5,%6,%7,%8,%9,%10,%11,%12,%13,%14,%15,%16,%17,%18,%19,"
        "%20,%21,%22,%23,%24,%25,%26,%27,%28,%29,%30,%31,%32,%33,%34,%35,%36,%37,%38,%39,"
        "%40,%41,%42,%43,%44,%45,%46,%47,%48,%49,%50,%51,%52,%53,%54,%55,%56,%57,%58,%59,"
        "%60,%61,%62,%63}, "
        "%64, %65, p, 1, 1, 0, 1;\n}\n"
        : "=f"(d[0]), "=f"(d[1]), "=f"(d[2]), "=f"(d[3]), "=f"(d[4]), "=f"(d[5]), "=f"(d[6]), "=f"(d[7]), "=f"(d[8]), "=f"(d[9]),
          "=f"(d[10]), "=f"(d[11]), "=f"(d[12]), "=f"(d[13]), "=f"(d[14]), "=f"(d[15]), "=f"(d[16]), "=f"(d[17]), "=f"(d[18]), "=f"(d[19]),
          "=f"(d[20]), "=f"(d[21]), "=f"(d[22]), "=f"(d[23]), "=f"(d[24]), "=f"(d[25]), "=f"(d[26]), "=f"(d[27]), "=f"(d[28]), "=f"(d[29]),
          "=f"(d[30]), "=f"(d[31]), "=f"(d[32]), "=f"(d[33]), "=f"(d[34]), "=f"(d[35]), "=f"(d[36]), "=f"(d[37]), "=f"(d[38]), "=f"(d[39]),
          "=f"(d[40]), "=f"(d[41]), "=f"(d[42]), "=f"(d[43]), "=f"(d[44]), "=f"(d[45]), "=f"(d[46]), "=f"(d[47]), "=f"(d[48]), "=f"(d[49]),
          "=f"(d[50]), "=f"(d[51]), "=f"(d[52]), "=f"(d[53]), "=f"(d[54]), "=f"(d[55]), "=f"(d[56]), "=f"(d[57]), "=f"(d[58]), "=f"(d[59]),
          "=f"(d[60]), "=f"(d[61]), "=f"(d[62]), "=f"(d[63])
        : "l"(da), "l"(db));
}
__device__ __forceinline__ void wgmma_ssf(float (&d)[56], uint64_t da, uint64_t db) {
    asm volatile("{\n.reg .pred p;\nsetp.ne.b32 p, 0, 0;\n"
        "wgmma.mma_async.sync.aligned.m64n112k16.f32.bf16.bf16 "
        "{%0,%1,%2,%3,%4,%5,%6,%7,%8,%9,%10,%11,%12,%13,%14,%15,%16,%17,%18,%19,"
        "%20,%21,%22,%23,%24,%25,%26,%27,%28,%29,%30,%31,%32,%33,%34,%35,%36,%37,%38,%39,"
        "%40,%41,%42,%43,%44,%45,%46,%47,%48,%49,%50,%51,%52,%53,%54,%55}, "
        "%56, %57, p, 1, 1, 0, 1;\n}\n"
        : "=f"(d[0]), "=f"(d[1]), "=f"(d[2]), "=f"(d[3]), "=f"(d[4]), "=f"(d[5]), "=f"(d[6]), "=f"(d[7]), "=f"(d[8]), "=f"(d[9]),
          "=f"(d[10]), "=f"(d[11]), "=f"(d[12]), "=f"(d[13]), "=f"(d[14]), "=f"(d[15]), "=f"(d[16]), "=f"(d[17]), "=f"(d[18]), "=f"(d[19]),
          "=f"(d[20]), "=f"(d[21]), "=f"(d[22]), "=f"(d[23]), "=f"(d[24]), "=f"(d[25]), "=f"(d[26]), "=f"(d[27]), "=f"(d[28]), "=f"(d[29]),
          "=f"(d[30]), "=f"(d[31]), "=f"(d[32]), "=f"(d[33]), "=f"(d[34]), "=f"(d[35]), "=f"(d[36]), "=f"(d[37]), "=f"(d[38]), "=f"(d[39]),
          "=f"(d[40]), "=f"(d[41]), "=f"(d[42]), "=f"(d[43]), "=f"(d[44]), "=f"(d[45]), "=f"(d[46]), "=f"(d[47]), "=f"(d[48]), "=f"(d[49]),
          "=f"(d[50]), "=f"(d[51]), "=f"(d[52]), "=f"(d[53]), "=f"(d[54]), "=f"(d[55])
        : "l"(da), "l"(db));
}
__device__ __forceinline__ void wgmma_ssf(float (&d)[24], uint64_t da, uint64_t db) {
    asm volatile("{\n.reg .pred p;\nsetp.ne.b32 p, 0, 0;\n"
        "wgmma.mma_async.sync.aligned.m64n48k16.f32.bf16.bf16 "
        "{%0,%1,%2,%3,%4,%5,%6,%7,%8,%9,%10,%11,%12,%13,%14,%15,%16,%17,%18,%19,"
        "%20,%21,%22,%23}, "
        "%24, %25, p, 1, 1, 0, 1;\n}\n"
        : "=f"(d[0]), "=f"(d[1]), "=f"(d[2]), "=f"(d[3]), "=f"(d[4]), "=f"(d[5]), "=f"(d[6]), "=f"(d[7]), "=f"(d[8]), "=f"(d[9]),
          "=f"(d[10]), "=f"(d[11]), "=f"(d[12]), "=f"(d[13]), "=f"(d[14]), "=f"(d[15]), "=f"(d[16]), "=f"(d[17]), "=f"(d[18]), "=f"(d[19]),
          "=f"(d[20]), "=f"(d[21]), "=f"(d[22]), "=f"(d[23])
        : "l"(da), "l"(db));
}
__device__ __forceinline__ void wgmma_rs80(float (&d)[40], uint32_t a0, uint32_t a1, uint32_t a2, uint32_t a3, uint64_t db) {
    asm volatile("{\n.reg .pred p;\nsetp.eq.b32 p, 0, 0;\n"
        "wgmma.mma_async.sync.aligned.m64n80k16.f32.bf16.bf16 "
        "{%0,%1,%2,%3,%4,%5,%6,%7,%8,%9,%10,%11,%12,%13,%14,%15,%16,%17,%18,%19,"
        "%20,%21,%22,%23,%24,%25,%26,%27,%28,%29,%30,%31,%32,%33,%34,%35,%36,%37,%38,%39}, "
        "{%40,%41,%42,%43}, %44, p, 1, 1, 1;\n}\n"
        : "+f"(d[0]), "+f"(d[1]), "+f"(d[2]), "+f"(d[3]), "+f"(d[4]), "+f"(d[5]), "+f"(d[6]), "+f"(d[7]), "+f"(d[8]), "+f"(d[9]),
          "+f"(d[10]), "+f"(d[11]), "+f"(d[12]), "+f"(d[13]), "+f"(d[14]), "+f"(d[15]), "+f"(d[16]), "+f"(d[17]), "+f"(d[18]), "+f"(d[19]),
          "+f"(d[20]), "+f"(d[21]), "+f"(d[22]), "+f"(d[23]), "+f"(d[24]), "+f"(d[25]), "+f"(d[26]), "+f"(d[27]), "+f"(d[28]), "+f"(d[29]),
          "+f"(d[30]), "+f"(d[31]), "+f"(d[32]), "+f"(d[33]), "+f"(d[34]), "+f"(d[35]), "+f"(d[36]), "+f"(d[37]), "+f"(d[38]), "+f"(d[39])
        : "r"(a0), "r"(a1), "r"(a2), "r"(a3), "l"(db));
}
__device__ __forceinline__ void wgmma_rs80f(float (&d)[40], uint32_t a0, uint32_t a1, uint32_t a2, uint32_t a3, uint64_t db) {
    asm volatile("{\n.reg .pred p;\nsetp.ne.b32 p, 0, 0;\n"
        "wgmma.mma_async.sync.aligned.m64n80k16.f32.bf16.bf16 "
        "{%0,%1,%2,%3,%4,%5,%6,%7,%8,%9,%10,%11,%12,%13,%14,%15,%16,%17,%18,%19,"
        "%20,%21,%22,%23,%24,%25,%26,%27,%28,%29,%30,%31,%32,%33,%34,%35,%36,%37,%38,%39}, "
        "{%40,%41,%42,%43}, %44, p, 1, 1, 1;\n}\n"
        : "=f"(d[0]), "=f"(d[1]), "=f"(d[2]), "=f"(d[3]), "=f"(d[4]), "=f"(d[5]), "=f"(d[6]), "=f"(d[7]), "=f"(d[8]), "=f"(d[9]),
          "=f"(d[10]), "=f"(d[11]), "=f"(d[12]), "=f"(d[13]), "=f"(d[14]), "=f"(d[15]), "=f"(d[16]), "=f"(d[17]), "=f"(d[18]), "=f"(d[19]),
          "=f"(d[20]), "=f"(d[21]), "=f"(d[22]), "=f"(d[23]), "=f"(d[24]), "=f"(d[25]), "=f"(d[26]), "=f"(d[27]), "=f"(d[28]), "=f"(d[29]),
          "=f"(d[30]), "=f"(d[31]), "=f"(d[32]), "=f"(d[33]), "=f"(d[34]), "=f"(d[35]), "=f"(d[36]), "=f"(d[37]), "=f"(d[38]), "=f"(d[39])
        : "r"(a0), "r"(a1), "r"(a2), "r"(a3), "l"(db));
}
__device__ __forceinline__ void wgmma_qk0(float (&d)[32], uint32_t a0, uint32_t a1, uint32_t a2, uint32_t a3, uint64_t db) {
    asm volatile("{\n.reg .pred p;\nsetp.ne.b32 p, 0, 0;\n"
        "wgmma.mma_async.sync.aligned.m64n64k16.f32.bf16.bf16 "
        "{%0,%1,%2,%3,%4,%5,%6,%7,%8,%9,%10,%11,%12,%13,%14,%15,%16,%17,%18,%19,"
        "%20,%21,%22,%23,%24,%25,%26,%27,%28,%29,%30,%31}, "
        "{%32,%33,%34,%35}, %36, p, 1, 1, 0;\n}\n"
        : "=f"(d[0]), "=f"(d[1]), "=f"(d[2]), "=f"(d[3]), "=f"(d[4]), "=f"(d[5]), "=f"(d[6]), "=f"(d[7]), "=f"(d[8]), "=f"(d[9]),
          "=f"(d[10]), "=f"(d[11]), "=f"(d[12]), "=f"(d[13]), "=f"(d[14]), "=f"(d[15]), "=f"(d[16]), "=f"(d[17]), "=f"(d[18]), "=f"(d[19]),
          "=f"(d[20]), "=f"(d[21]), "=f"(d[22]), "=f"(d[23]), "=f"(d[24]), "=f"(d[25]), "=f"(d[26]), "=f"(d[27]), "=f"(d[28]), "=f"(d[29]),
          "=f"(d[30]), "=f"(d[31])
        : "r"(a0), "r"(a1), "r"(a2), "r"(a3), "l"(db));
}
__device__ __forceinline__ void wgmma_qk1(float (&d)[32], uint32_t a0, uint32_t a1, uint32_t a2, uint32_t a3, uint64_t db) {
    asm volatile("{\n.reg .pred p;\nsetp.eq.b32 p, 0, 0;\n"
        "wgmma.mma_async.sync.aligned.m64n64k16.f32.bf16.bf16 "
        "{%0,%1,%2,%3,%4,%5,%6,%7,%8,%9,%10,%11,%12,%13,%14,%15,%16,%17,%18,%19,"
        "%20,%21,%22,%23,%24,%25,%26,%27,%28,%29,%30,%31}, "
        "{%32,%33,%34,%35}, %36, p, 1, 1, 0;\n}\n"
        : "+f"(d[0]), "+f"(d[1]), "+f"(d[2]), "+f"(d[3]), "+f"(d[4]), "+f"(d[5]), "+f"(d[6]), "+f"(d[7]), "+f"(d[8]), "+f"(d[9]),
          "+f"(d[10]), "+f"(d[11]), "+f"(d[12]), "+f"(d[13]), "+f"(d[14]), "+f"(d[15]), "+f"(d[16]), "+f"(d[17]), "+f"(d[18]), "+f"(d[19]),
          "+f"(d[20]), "+f"(d[21]), "+f"(d[22]), "+f"(d[23]), "+f"(d[24]), "+f"(d[25]), "+f"(d[26]), "+f"(d[27]), "+f"(d[28]), "+f"(d[29]),
          "+f"(d[30]), "+f"(d[31])
        : "r"(a0), "r"(a1), "r"(a2), "r"(a3), "l"(db));
}
__device__ __forceinline__ void wgmma_pv(float (&d)[12], uint32_t a0, uint32_t a1, uint32_t a2, uint32_t a3, uint64_t db) {
    asm volatile("{\n.reg .pred p;\nsetp.eq.b32 p, 0, 0;\n"
        "wgmma.mma_async.sync.aligned.m64n24k16.f32.bf16.bf16 "
        "{%0,%1,%2,%3,%4,%5,%6,%7,%8,%9,%10,%11}, "
        "{%12,%13,%14,%15}, %16, p, 1, 1, 1;\n}\n"
        : "+f"(d[0]), "+f"(d[1]), "+f"(d[2]), "+f"(d[3]), "+f"(d[4]), "+f"(d[5]), "+f"(d[6]), "+f"(d[7]), "+f"(d[8]), "+f"(d[9]),
          "+f"(d[10]), "+f"(d[11])
        : "r"(a0), "r"(a1), "r"(a2), "r"(a3), "l"(db));
}
__device__ __forceinline__ void wgmma_pvn(float (&d)[12], uint32_t a0, uint32_t a1, uint32_t a2, uint32_t a3, uint64_t db) {
    asm volatile("{\n.reg .pred p;\nsetp.eq.b32 p, 0, 0;\n"
        "wgmma.mma_async.sync.aligned.m64n24k16.f32.bf16.bf16 "
        "{%0,%1,%2,%3,%4,%5,%6,%7,%8,%9,%10,%11}, "
        "{%12,%13,%14,%15}, %16, p, -1, 1, 1;\n}\n"
        : "+f"(d[0]), "+f"(d[1]), "+f"(d[2]), "+f"(d[3]), "+f"(d[4]), "+f"(d[5]), "+f"(d[6]), "+f"(d[7]), "+f"(d[8]), "+f"(d[9]),
          "+f"(d[10]), "+f"(d[11])
        : "r"(a0), "r"(a1), "r"(a2), "r"(a3), "l"(db));
}
__device__ __forceinline__ void wgmma_pv0(float (&d)[12], uint32_t a0, uint32_t a1, uint32_t a2, uint32_t a3, uint64_t db) {
    asm volatile("{\n.reg .pred p;\nsetp.ne.b32 p, 0, 0;\n"
        "wgmma.mma_async.sync.aligned.m64n24k16.f32.bf16.bf16 "
        "{%0,%1,%2,%3,%4,%5,%6,%7,%8,%9,%10,%11}, "
        "{%12,%13,%14,%15}, %16, p, 1, 1, 1;\n}\n"
        : "=f"(d[0]), "=f"(d[1]), "=f"(d[2]), "=f"(d[3]), "=f"(d[4]), "=f"(d[5]), "=f"(d[6]), "=f"(d[7]), "=f"(d[8]), "=f"(d[9]),
          "=f"(d[10]), "=f"(d[11])
        : "r"(a0), "r"(a1), "r"(a2), "r"(a3), "l"(db));
}
__device__ __forceinline__ void wgmma_l64a(float (&d)[32], uint64_t da, uint64_t db) {
    asm volatile("{\n.reg .pred p;\nsetp.ne.b32 p, 0, 0;\n"
        "wgmma.mma_async.sync.aligned.m64n64k16.f32.bf16.bf16 "
        "{%0,%1,%2,%3,%4,%5,%6,%7,%8,%9,%10,%11,%12,%13,%14,%15,%16,%17,%18,%19,"
        "%20,%21,%22,%23,%24,%25,%26,%27,%28,%29,%30,%31}, "
        "%32, %33, p, 1, 1, 0, 0;\n}\n"
        : "=f"(d[0]), "=f"(d[1]), "=f"(d[2]), "=f"(d[3]), "=f"(d[4]), "=f"(d[5]), "=f"(d[6]), "=f"(d[7]), "=f"(d[8]), "=f"(d[9]),
          "=f"(d[10]), "=f"(d[11]), "=f"(d[12]), "=f"(d[13]), "=f"(d[14]), "=f"(d[15]), "=f"(d[16]), "=f"(d[17]), "=f"(d[18]), "=f"(d[19]),
          "=f"(d[20]), "=f"(d[21]), "=f"(d[22]), "=f"(d[23]), "=f"(d[24]), "=f"(d[25]), "=f"(d[26]), "=f"(d[27]), "=f"(d[28]), "=f"(d[29]),
          "=f"(d[30]), "=f"(d[31])
        : "l"(da), "l"(db));
}
__device__ __forceinline__ void wgmma_l64b(float (&d)[32], uint64_t da, uint64_t db) {
    asm volatile("{\n.reg .pred p;\nsetp.eq.b32 p, 0, 0;\n"
        "wgmma.mma_async.sync.aligned.m64n64k16.f32.bf16.bf16 "
        "{%0,%1,%2,%3,%4,%5,%6,%7,%8,%9,%10,%11,%12,%13,%14,%15,%16,%17,%18,%19,"
        "%20,%21,%22,%23,%24,%25,%26,%27,%28,%29,%30,%31}, "
        "%32, %33, p, 1, 1, 0, 0;\n}\n"
        : "+f"(d[0]), "+f"(d[1]), "+f"(d[2]), "+f"(d[3]), "+f"(d[4]), "+f"(d[5]), "+f"(d[6]), "+f"(d[7]), "+f"(d[8]), "+f"(d[9]),
          "+f"(d[10]), "+f"(d[11]), "+f"(d[12]), "+f"(d[13]), "+f"(d[14]), "+f"(d[15]), "+f"(d[16]), "+f"(d[17]), "+f"(d[18]), "+f"(d[19]),
          "+f"(d[20]), "+f"(d[21]), "+f"(d[22]), "+f"(d[23]), "+f"(d[24]), "+f"(d[25]), "+f"(d[26]), "+f"(d[27]), "+f"(d[28]), "+f"(d[29]),
          "+f"(d[30]), "+f"(d[31])
        : "l"(da), "l"(db));
}
__device__ __forceinline__ void wgmma_l16a(float (&d)[8], uint64_t da, uint64_t db) {
    asm volatile("{\n.reg .pred p;\nsetp.ne.b32 p, 0, 0;\n"
        "wgmma.mma_async.sync.aligned.m64n16k16.f32.bf16.bf16 "
        "{%0,%1,%2,%3,%4,%5,%6,%7}, "
        "%8, %9, p, 1, 1, 0, 0;\n}\n"
        : "=f"(d[0]), "=f"(d[1]), "=f"(d[2]), "=f"(d[3]), "=f"(d[4]), "=f"(d[5]), "=f"(d[6]), "=f"(d[7])
        : "l"(da), "l"(db));
}
__device__ __forceinline__ void wgmma_l16b(float (&d)[8], uint64_t da, uint64_t db) {
    asm volatile("{\n.reg .pred p;\nsetp.eq.b32 p, 0, 0;\n"
        "wgmma.mma_async.sync.aligned.m64n16k16.f32.bf16.bf16 "
        "{%0,%1,%2,%3,%4,%5,%6,%7}, "
        "%8, %9, p, 1, 1, 0, 0;\n}\n"
        : "+f"(d[0]), "+f"(d[1]), "+f"(d[2]), "+f"(d[3]), "+f"(d[4]), "+f"(d[5]), "+f"(d[6]), "+f"(d[7])
        : "l"(da), "l"(db));
}

__device__ __forceinline__ uint32_t exp2_pair_fma(float a, float b) {
    const uint32_t y = __byte_perm(__float_as_uint(a), __float_as_uint(b), 0x6521);
    const uint32_t z = 0xFE7BFE7Bu - y;
    const uint32_t e = hfma2(y, z, 0x3F053F05u);
    return hfma2(y, e, y);
}
__device__ __forceinline__ void qk_tile(float (&s)[32], const uint32_t (&q)[8], uint64_t dk0, uint64_t dk1) {
    wgmma_qk0(s, q[0], q[1], q[2], q[3], dk0);
    wgmma_qk1(s, q[4], q[5], q[6], q[7], dk1);
}
__device__ __forceinline__ void exp_pv_tile(const float (&s)[32], uint32_t (&p)[16], float (&o)[12], uint64_t dv, const int mask) {
    auto ex = [&](int j) {
        if ((mask >> (j >> 1)) & 1) { p[2 * j] = exp2_pair_fma(s[4 * j], s[4 * j + 1]); p[2 * j + 1] = exp2_pair_fma(s[4 * j + 2], s[4 * j + 3]); }
        else { p[2 * j] = pack2(ex2(s[4 * j]), ex2(s[4 * j + 1])); p[2 * j + 1] = pack2(ex2(s[4 * j + 2]), ex2(s[4 * j + 3])); }
    };
    auto pv = [&](int k) {
        if ((mask >> k) & 1) wgmma_pvn(o, p[4 * k], p[4 * k + 1], p[4 * k + 2], p[4 * k + 3], dv + k * 48);
        else wgmma_pv(o, p[4 * k], p[4 * k + 1], p[4 * k + 2], p[4 * k + 3], dv + k * 48);
    };
    auto hold = [&](int j) { asm volatile("" : "+r"(p[2 * j]), "+r"(p[2 * j + 1])::"memory"); };
    ex(2); ex(0); ex(1); hold(2);
    wg_fence(); pv(0);
    ex(3); ex(4); ex(5); ex(6); ex(7);
    wg_fence(); pv(1); pv(2); pv(3);
    wg_commit();
}
__device__ __forceinline__ void finish_o(const float (&o)[12], uint32_t (&w)[6], int odd, float g0, float g1, int lane, float& l0, float& l1) {
    const int src = (lane & ~3) | (odd ? 0 : 2);
    l0 = __shfl_sync(0xffffffffu, o[8], src);
    l1 = __shfl_sync(0xffffffffu, o[10], src);
    float r0, r1;
    asm("rcp.approx.ftz.f32 %0, %1;" : "=f"(r0) : "f"(l0));
    asm("rcp.approx.ftz.f32 %0, %1;" : "=f"(r1) : "f"(l1));
    const float f0 = g0 * r0, f1 = g1 * r1;
#pragma unroll
    for (int d = 0; d < 3; d++) { w[2 * d] = pack2(o[4 * d] * f0, o[4 * d + 1] * f0); w[2 * d + 1] = pack2(o[4 * d + 2] * f1, o[4 * d + 3] * f1); }
}
struct OutPtr { uint8_t *p01, *p2; bool has2; };
__device__ __forceinline__ OutPtr out_ptr(uint32_t row16, uint32_t h, uint32_t gbase, uint32_t lane) {
    uint8_t* base = reinterpret_cast<uint8_t*>(g_att) + ((row16 >> 2) * 163840u + gbase * 1024u + h * 2560u + (row16 & 3) * 128u);
    const uint32_t pos = (lane >> 2) * 16 + (lane & 1) * 8, odd = h & 1, hi = (lane >> 1) & 1;
    return {base + (pos + (hi + odd) * 512), base + (pos + (odd ? 0 : 2048)), hi == odd};
}
__device__ __forceinline__ void store_o(const uint32_t (&w)[6], const OutPtr& o, int off) {
    stg64(o.p01 + off, w[0], w[1]);
    stg64(o.p01 + off + 1024, w[2], w[3]);
    if (o.has2) stg64(o.p2 + off, w[4], w[5]);
}

__device__ __forceinline__ int p1_mp(int bid) { return (bid >> 1) & 7; }
__device__ __forceinline__ int p1_nt(int bid) { return bid >> 4; }
__device__ __forceinline__ int p1_nta(int nt) { return (nt + 4) & 7; }
constexpr uint32_t PACE = 280, G1 = 500, G2 = 1200;
constexpr int LJ = 16;
constexpr uint32_t SB0 = 1024;
constexpr int SLOT = 24576;
constexpr int OFF_X = 98304, OFF_R = 6 * SLOT, OFF_L = OFF_R - 1536, OFF_BAR = 9 * SLOT;
constexpr int OFF_F = OFF_BAR + 1024 + 128, SMEM_BYTES = OFF_F + 8192;
enum { B_FULL = 0, B_EMPTY = 48, B_STGB = 96, B_STGA = 104, B_RET = 112, B_NRM = 144, B_HLP = 152, B_KV = 160, B_HDR = 192, B_L = 200, B_WO = 208, B_XCH = 248, B_AF = 264, B_LD = 328, B_R26 = 336, B_AE = 344, B_STG1 = 352, B_W0 = 376, B_ZERO = 400, B_MISC = 416, B_PUB = 1024 };
__host__ __device__ constexpr int k_off(int j) {
    return j < 8 ? (7 + (j >> 2)) * SLOT + (j & 3) * 3072 : j == 8 ? OFF_R - 6144 : j < 20 ? 3 * SLOT + (j - 9) * 3072 : j < 26 ? 36864 + (j - 20) * 3072 : (j - 26) * 3072;
}
__host__ __device__ constexpr int v_off(int j) { return k_off(j) + (j < 8 ? 4 : j == 8 ? 1 : j < 20 ? 11 : 6) * 3072; }
__host__ __device__ constexpr int wo_off(int i) { return 3 * SLOT + (i < 7 ? i : i - 7) * 20480; }
__host__ __device__ constexpr int wo_bar(int i) { return i < 3 ? 0 : i < 7 ? 1 : i - 5; }
constexpr float SCORE_LIMIT2 = 118.f * 118.f;

__device__ __forceinline__ void load_kv(uint32_t sb, int h, int i, int j0, int n, int arm) {
    const uint32_t bar = sb + OFF_BAR + B_KV + 8 * i;
    if (arm) mbar_expect_tx(bar, arm * 6144);
    bulk_g2s(sb + k_off(j0), g_qkv + (size_t)(32 + h) * HEAD_BYTES + j0 * 3072, n * 3072, bar);
    bulk_g2s(sb + v_off(j0), g_qkv + (size_t)(64 + h) * HEAD_BYTES + j0 * 3072, n * 3072, bar);
}
__device__ __forceinline__ void load_wo(uint32_t sb, int seq, int n) {
    const uint32_t bar = sb + OFF_BAR + B_WO + 8 * wo_bar(seq);
    mbar_expect_tx(bar, n * 20480);
    bulk_g2s(sb + wo_off(seq), reinterpret_cast<const uint8_t*>(g_wo) + (blockIdx.x & 7) * 204800 + seq * 20480, n * 20480, bar);
}

__device__ __forceinline__ void local_attn(uint32_t sb, uint32_t wid, uint64_t dK0, uint64_t dK1, uint64_t dV) {
    const uint32_t tid = fresh_tid(), lane = tid & 31, g = lane >> 2, t2 = (lane & 3) * 2;
    const uint32_t wg = wid >> 2, w = wid & 3;
    const uint32_t bid = fresh_bid(), h = bid >> 2, qb = bid & 3;
    const float* gp = g_gate + (qb * 512 + wg * 128 + w * 16) + g;
    const float gt[4] = {ldcg_f32(gp), ldcg_f32(gp + 8), ldcg_f32(gp + 64), ldcg_f32(gp + 72)};
    const bool cur0 = t2 <= g, cur1 = t2 < g;
    mbar_wait(sb + OFF_BAR + B_L, 0);
    const uint32_t mc = (cur0 ? 0xffffu : 0u) | (cur1 ? 0xffff0000u : 0u);
    uint32_t mk[5];
    float v0[4], v1[4];
    {
        const uint64_t dq0 = dK0 + ((OFF_L >> 4) + wg * 384), dq1 = dK1 + ((OFF_L >> 4) + wg * 384);
        float sa[2][32], sc[2][8];
        wg_fence();
#pragma unroll
        for (int b = 0; b < 2; b++) {
            wgmma_l64a(sa[b], dq0 + b * 192, dq0 + b * 192 + (24576 >> 4)); wgmma_l64b(sa[b], dq1 + b * 192, dq1 + b * 192 + (24576 >> 4));
            wgmma_l16a(sc[b], dq0 + b * 192, dq0 + b * 192 + (27648 >> 4)); wgmma_l16b(sc[b], dq1 + b * 192, dq1 + b * 192 + (27648 >> 4));
        }
        wg_commit(); wg_wait<0>(); pin(sa[0]); pin(sa[1]); pin(sc[0]); pin(sc[1]);
#define LS(B, BLK, R, E) ((BLK) < 4 ? sa[B][((BLK) * 8 + (R) * 6 + (E)) & 31] : sc[B][(R) * 6 + (E)])
#define LWIN(W) { _Pragma("unroll") for (int i = 0; i < 4; i++) { v0[i] = cur0 ? LS(i >> 1, (W) + 1, i & 1, 0) : LS(i >> 1, W, i & 1, 0); \
                                                                 v1[i] = cur1 ? LS(i >> 1, (W) + 1, i & 1, 1) : LS(i >> 1, W, i & 1, 1); } \
                  _Pragma("unroll") for (int ks = 0; ks < 5; ks++) mk[ks] = ks == (W) ? ~mc : ks == (W) + 1 ? mc : 0u; pin(mk); }
        if (w == 0) LWIN(0) else if (w == 1) LWIN(1) else if (w == 2) LWIN(2) else LWIN(3)
#undef LWIN
#undef LS
    }
    if (qb == 0 && wid == 0) {
        if (!cur0) v0[0] = v0[1] = -INFINITY;
        if (!cur1) v1[0] = v1[1] = -INFINITY;
    }
    float m[4], l[4];
#pragma unroll
    for (int i = 0; i < 4; i++) m[i] = fmaxf(v0[i], v1[i]);
#pragma unroll
    for (int i = 0; i < 4; i++) m[i] = fmaxf(m[i], __shfl_xor_sync(0xffffffffu, m[i], 1));
#pragma unroll
    for (int i = 0; i < 4; i++) m[i] = fmaxf(m[i], __shfl_xor_sync(0xffffffffu, m[i], 2));
#pragma unroll
    for (int i = 0; i < 4; i++) { v0[i] = ex2(v0[i] - m[i]); v1[i] = ex2(v1[i] - m[i]); l[i] = v0[i] + v1[i]; }
#pragma unroll
    for (int i = 0; i < 4; i++) l[i] += __shfl_xor_sync(0xffffffffu, l[i], 1);
#pragma unroll
    for (int i = 0; i < 4; i++) l[i] += __shfl_xor_sync(0xffffffffu, l[i], 2);
    uint32_t pp[4];
#pragma unroll
    for (int i = 0; i < 4; i++) {
        float r;
        asm("rcp.approx.ftz.f32 %0, %1;" : "=f"(r) : "f"(l[i]));
        r *= gt[i];
        pp[i] = pack2(v0[i] * r, v1[i] * r);
    }
    uint32_t p[2][20];
#pragma unroll
    for (int ks = 0; ks < 5; ks++) {
#pragma unroll
        for (int b = 0; b < 2; b++) { p[b][4 * ks] = pp[2 * b] & mk[ks]; p[b][4 * ks + 1] = p[b][4 * ks + 2] = 0u; p[b][4 * ks + 3] = pp[2 * b + 1] & mk[ks]; }
    }
    pin(p[0]); pin(p[1]);
    const uint64_t dv = dV + (((OFF_L + 24576 + 25344) >> 4) + wg * 384);
    float o[2][12];
    wg_fence();
#pragma unroll
    for (int b = 0; b < 2; b++) {
        wgmma_pv0(o[b], p[b][0], p[b][1], p[b][2], p[b][3], dv + b * 192);
#pragma unroll
        for (int ks = 1; ks < 5; ks++) wgmma_pv(o[b], p[b][4 * ks], p[b][4 * ks + 1], p[b][4 * ks + 2], p[b][4 * ks + 3], dv + b * 192 + ks * 48);
    }
    wg_commit();
    const OutPtr op = out_ptr(qb * 32 + wg * 8 + w, h, 0, lane);
    wg_wait<0>(); pin(o[0]); pin(o[1]);
#pragma unroll
    for (int b = 0; b < 2; b++) {
        uint32_t wv[6];
#pragma unroll
        for (int i = 0; i < 6; i++) wv[i] = pack2(o[b][2 * i], o[b][2 * i + 1]);
        store_o(wv, op, b * 163840);
    }
    __syncwarp();
    if (elect_one()) mbar_arrive(sb + OFF_BAR + B_LD);
}

__device__ __noinline__ void exact_rows(int h, int row16, int lane) {
    const bool aug_lane = ((lane & 3) >= 2) != ((h & 1) != 0);
    const uint8_t* a = g_qkv + (size_t)h * HEAD_BYTES + row16 * 768 + lane * 4;
    const uint8_t* gk = g_qkv + (size_t)(32 + h) * HEAD_BYTES + lane * 4;
    const uint8_t* gv = g_qkv + (size_t)(64 + h) * HEAD_BYTES + lane * 4;
    const uint32_t q0 = ldcg_u32(a), q1 = ldcg_u32(a + 384), q2 = ldcg_u32(a + 128), q3 = ldcg_u32(a + 512);
    const uint32_t q4 = aug_lane ? 0u : ldcg_u32(a + 256), q5 = aug_lane ? 0u : ldcg_u32(a + 640);
    float m0 = -INFINITY, m1 = -INFINITY;
#pragma unroll 4
    for (int kg = 0; kg < 256; kg++) {
        const uint8_t* ka = gk + kg * 384;
        float c[4] = {0.f, 0.f, 0.f, 0.f};
        mma16816(c, q0, q1, q2, q3, ldcg_u32(ka), ldcg_u32(ka + 128));
        mma1688(c, q4, q5, ldcg_u32(ka + 256));
        m0 = fmaxf(m0, fmaxf(c[0], c[1])); m1 = fmaxf(m1, fmaxf(c[2], c[3]));
    }
    m0 = fmaxf(m0, __shfl_xor_sync(0xffffffffu, m0, 1)); m1 = fmaxf(m1, __shfl_xor_sync(0xffffffffu, m1, 1));
    m0 = fmaxf(m0, __shfl_xor_sync(0xffffffffu, m0, 2)); m1 = fmaxf(m1, __shfl_xor_sync(0xffffffffu, m1, 2));
    float oc[3][4];
#pragma unroll
    for (int d = 0; d < 3; d++) oc[d][0] = oc[d][1] = oc[d][2] = oc[d][3] = 0.f;
#pragma unroll 2
    for (int kg = 0; kg < 256; kg += 2) {
        uint32_t kk[2][3], vv[2][3], pp[2][2];
#pragma unroll
        for (int e = 0; e < 2; e++)
#pragma unroll
            for (int d = 0; d < 3; d++) { kk[e][d] = ldcg_u32(gk + (kg + e) * 384 + d * 128); vv[e][d] = ldcg_u32(gv + (kg + e) * 384 + d * 128); }
#pragma unroll
        for (int e = 0; e < 2; e++) {
            float c[4] = {0.f, 0.f, 0.f, 0.f};
            mma16816(c, q0, q1, q2, q3, kk[e][0], kk[e][1]);
            mma1688(c, q4, q5, kk[e][2]);
            pp[e][0] = pack2(ex2(c[0] - m0), ex2(c[1] - m0));
            pp[e][1] = pack2(ex2(c[2] - m1), ex2(c[3] - m1));
        }
#pragma unroll
        for (int d = 0; d < 3; d++) mma16816(oc[d], pp[0][0], pp[0][1], pp[1][0], pp[1][1], movm_t(vv[0][d]), movm_t(vv[1][d]));
    }
    float o[12];
#pragma unroll
    for (int i = 0; i < 12; i++) o[i] = oc[i >> 2][i & 3];
    const int row = row16 * 16 + (lane >> 2);
    float l0, l1;
    uint32_t w[6];
    finish_o(o, w, h & 1, 1.f - ldcg_f32(g_gate + row), 1.f - ldcg_f32(g_gate + row + 8), lane, l0, l1);
    store_o(w, out_ptr(row16, h, 80, lane), 0);
}


__device__ __forceinline__ uint32_t frag_off(int mh, int item) {
    return item < 5 ? 40960 + (mh * 2 + item) * 8192 : (item == 9 && mh) ? OFF_F : mh * 40960 + (item - 5) * 8192;
}
__device__ __forceinline__ void load_frag(uint32_t sb, int bid, int mh, int part) {
    const uint32_t fb = sb + OFF_BAR + B_AF + mh * 32 + part * 8;
    const uint2* src = g_att + (((bid >> 5) * 8 + mh * 4 + ((bid >> 3) & 3)) * 160 + (bid & 1) * 40 + (part ? 64 + part * 16 : 0)) * 128;
    if (part == 0) mbar_expect_tx(fb, 16384);
    bulk_g2s(sb + frag_off(mh, part ? 3 + 2 * part : 0), src, (part == 2 && !mh) ? 24576 : 16384, fb);
    if (part == 2 && mh) bulk_g2s(sb + OFF_F, src + 2048, 8192, fb);
}
__device__ __forceinline__ uint32_t* atta_out(int bid) { return g_flag + (F_ATTA + (bid & 3) * 2 + (bid >> 6)) * 32; }
__device__ __forceinline__ uint32_t* attb_out(int bid, int wg) { return g_flag + (F_ATTB + ((bid & 3) * 4 + wg) * 2 + (bid >> 6)) * 32; }
__device__ __forceinline__ uint32_t* atta_in(int bid) { return g_flag + (F_ATTA + (bid >> 5) * 2 + (bid & 1)) * 32; }
__device__ __forceinline__ uint32_t* attb_in(int bid) { return g_flag + (F_ATTB + (bid >> 3) * 2 + (bid & 1)) * 32; }
__device__ __forceinline__ void service(uint32_t sb, int step, uint32_t aflag) {
    const uint32_t bars = sb + OFF_BAR;
    const int bid = fresh_bid(), h = bid >> 2, qb = bid & 3;
    if (step == 0) {
        bulk_wait_all();
        flag_add_done(g_flag + (F_QKVA + p1_nta(p1_nt(bid))) * 32);
        load_kv(sb, h, 3, 20, 6, 12); load_kv(sb, h, 3, 26, 6, 0);
    } else if (step == 3) {
        mbar_wait(bars + B_RET + 24, 0);
        load_wo(sb, 0, 3); load_wo(sb, 3, 4);
    } else if (step == 4) {
        mbar_wait(bars + B_LD, 0);
        flag_add_done(atta_out(bid));
    } else if (step == 2) {
        if (aflag >= 16) {
            mbar_wait(bars + B_R26, 0);
            asm volatile("fence.acquire.gpu;" ::: "memory");
            load_frag(sb, bid, 0, 0); load_frag(sb, bid, 1, 0);
        }
    } else {
        mbar_wait(bars + B_RET, 0);
        fence_async_smem();
        const int halo = qb ? 768 : 0;
        const uint8_t* src = g_qkv + (size_t)(96 + h) * HEAD_BYTES + qb * 24576;
        mbar_expect_tx(bars + B_L, 3 * 24576 + 2 * halo);
        bulk_g2s(sb + OFF_L, src, 24576, bars + B_L);
        bulk_g2s(sb + OFF_L + 24576 + 768 - halo, src + (size_t)32 * HEAD_BYTES - halo, 24576 + halo, bars + B_L);
        bulk_g2s(sb + OFF_L + 24576 + 25344 + 768 - halo, src + (size_t)64 * HEAD_BYTES - halo, 24576 + halo, bars + B_L);
    }
}

template <bool B> struct Bool { static constexpr bool value = B; };
struct WBox { const CUtensorMap* tm; int c0, c1; };
__device__ __forceinline__ WBox w_box(const CUtensorMap* tw, const CUtensorMap* tg, int t, int at) {
    if (t < 6) return {tw, at * 64, t};
    if (at < 3) return {tw, 256, (t - 6) * 3 + at};
    return {tg, 0, (t - 6) * 3};
}

__global__ void __cluster_dims__(2, 1, 1) __launch_bounds__(512, 1)
k_fused(const __grid_constant__ CUtensorMap tmX, const __grid_constant__ CUtensorMap tmWb, const __grid_constant__ CUtensorMap tmWa,
        const __grid_constant__ CUtensorMap tmGb, const __grid_constant__ CUtensorMap tmGa,
        const __grid_constant__ CUtensorMap tmS, const __nv_bfloat16* __restrict__ x, const __nv_bfloat16* __restrict__ gate_w,
        const uint8_t* __restrict__ wb, const uint8_t* __restrict__ woa, const uint8_t* __restrict__ wob,
        __nv_bfloat16* __restrict__ out) {
    extern __shared__ __align__(1024) uint8_t smem_raw[];
    const uint32_t sb = smem_u32(smem_raw);
    if ((sb & 0xFFFFFFu) != SB0) __trap();
    const uint32_t bars = sb + OFF_BAR;
    float* s_misc = reinterpret_cast<float*>(smem_raw + OFF_BAR + B_MISC);
    const int bid = blockIdx.x;
    const int h = bid >> 2, qb = bid & 3;

    {
        const int warp = __shfl_sync(0xffffffffu, threadIdx.x >> 5, 0), lane = threadIdx.x & 31;
        const int mt = p1_mp(bid) * 2 + (bid & 1), nt = p1_nt(bid);
        if (warp >= 12 && warp < 14) {
            if (lane < 15) asm volatile("prefetch.global.L2 [%0];" ::"l"(wb + (warp - 12) * 245760 + bid * 1920 + lane * 128) : "memory");
            if (lane >= 16) asm volatile("prefetch.global.L2 [%0];" ::"l"(x + (size_t)(bid * 16 + lane - 16) * DM + (warp - 12) * 64) : "memory");
        }
        if (threadIdx.x == 352) {
            prefetch_tmap(&tmX);
#pragma unroll
            for (int i = 0; i < 6; i++) mbar_init(bars + B_FULL + 8 * i, 1);
            fence_mbar_init();
        } else if (threadIdx.x == 256) {
            prefetch_tmap(&tmWb); prefetch_tmap(&tmGb);
        } else if (threadIdx.x == 32) {
#pragma unroll
            for (int i = 0; i < 6; i++) mbar_init(bars + B_EMPTY + 8 * i, 16);
#pragma unroll
            for (int i = 0; i < 4; i++) mbar_init(bars + B_PUB + 8 * i, 4);
            fence_mbar_init();
        } else if (threadIdx.x == 64) {
            mbar_init(bars + B_STGB, 4); mbar_init(bars + B_STG1, 4); mbar_init(bars + B_STGA, 8);
            mbar_init(bars + B_RET, 16); mbar_init(bars + B_RET + 8, 8); mbar_init(bars + B_RET + 16, 16); mbar_init(bars + B_RET + 24, 16);
            mbar_init(bars + B_LD, 16); mbar_init(bars + B_NRM, 4); mbar_init(bars + B_HLP, 4);
            fence_mbar_init();
        } else if (threadIdx.x == 128) {
#pragma unroll
            for (int i = 0; i < 10; i++) mbar_init(bars + B_XCH + 8 * i, 1);
            fence_mbar_init();
#pragma unroll
            for (int i = 0; i < 2; i++) {
                mbar_expect_tx(bars + B_XCH + 8 * i, 10240);
                mbar_expect_tx(bars + B_AF + 32 * i + 8, 16384); mbar_expect_tx(bars + B_AF + 32 * i + 16, 24576);
            }
        } else if (threadIdx.x == 160) {
            mbar_init(bars + B_AE, 8); mbar_init(bars + B_R26, 16); mbar_init(bars + B_W0, 8); mbar_init(bars + B_W0 + 8, 8); mbar_init(bars + B_W0 + 16, 8);
            fence_mbar_init();
        } else if (threadIdx.x == 96) {
#pragma unroll
            for (int i = 0; i < 11; i++) mbar_init(bars + B_KV + 8 * i, i == 3 ? 2 : 1);
            s_misc[-4] = 0.f; s_misc[-3] = 0.f;
            fence_mbar_init();
        }
        __syncwarp();
        cluster_arrive();
        if (warp == 11 && elect_one()) {
            tma_x(sb + OFF_X, &tmX, 0, mt * 8, bars + B_FULL);
#pragma unroll
            for (int i = 0; i < 6; i++) mbar_expect_tx(bars + B_FULL + 8 * i, (i & 1) ? 16384 : 32768);
        }
        __syncwarp();
        cluster_wait();
        const uint32_t t_start = clock_lo();
        if ((warp == 8 || warp == 10) && elect_one()) {
            const int at = (bid & 1) * 2 + (warp == 10);
            const WBox bx = w_box(&tmWb, &tmGb, nt, at);
#pragma unroll
            for (int i = 0; i < 2; i++) tma_3d_mc(sb + i * 16384 + at * 4096, bx.tm, bx.c0, i * 32, bx.c1, bars + B_FULL + 8 * i, 3);
        }
        __syncwarp();

        if (warp < 8) {
            asm volatile("setmaxnreg.inc.sync.aligned.u32 152;");
            const int wg = warp >> 2, t = lane & 3;
            const uint64_t da0 = mkdesc(SB0 + OFF_X, 16, 1024, 1) + wg * 512, db0 = mkdesc(SB0, 4096, 1024, 1);
            uint32_t rel;
            asm volatile("mapa.shared::cluster.u32 %0, %1, %2;" : "=r"(rel) : "r"(bars + B_EMPTY), "r"(lane & 1));
            uint32_t xs = 0, xprev = 0, ph = 0;
#pragma unroll 1
            for (int br = 0; br < 2; br++) {
                const int ct = br ? p1_nta(nt) : nt;
                auto tile = [&](auto gathered) {
                    constexpr bool G = decltype(gathered)::value;
                    constexpr int N0 = G ? 96 : 64;
                    float acc0[N0], acc1[120 - N0];
                    constexpr uint64_t dc0 = G ? mkdesc(SB0 + 12288, 1024, 256, 3) : mkdesc(SB0 + 8192, 4096, 1024, 1);
                    constexpr uint32_t dck = G ? 32 : 128;
                    bool last = false;
                    auto pair = [&](bool first) {
                        const uint64_t da = da0 + xs * 1024, db = db0 + xs * 2048, dc = dc0 + xs * 2048, dd = dc + dck;
#pragma unroll
                        for (int e = 0; e < 2; e++) {
                            mbar_wait(bars + B_FULL + 16 * xs + 8 * e, ph);
                            wg_fence();
                            if (first && e == 0) { wgmma_ssf(acc0, da, db); wgmma_ssf(acc1, da, dc); }
                            else { wgmma_ss(acc0, da + e * 4, db + e * 1024); wgmma_ss(acc1, da + e * 4, dc + e * 1024); }
                            wgmma_ss(acc0, da + e * 4 + 2, db + e * 1024 + 128);
                            wgmma_ss(acc1, da + e * 4 + 2, dd + e * 1024);
                            wg_commit();
                            if (!first && e == 0 && last) asm volatile("bar.arrive 2, 256;" ::: "memory");
                            if (!first || e) {
                                wg_wait<1>();
                                if (lane < 2) asm volatile("mbarrier.arrive.shared::cluster.b64 _, [%0];" ::"r"(e ? rel + 16 * xs : rel + 16 * xprev + 8) : "memory");
                            }
                        }
                        xprev = xs;
                        if (++xs == 3) { xs = 0; ph ^= 1; }
                    };
                    pair(true);
#pragma unroll 1
                    for (int kp = 1; kp < 10; kp++) {
                        if (kp == 8 && br == 0 && wg == 1) named_sync(2, 256);
                        last = kp == 9 && br == 0 && wg == 0;
                        pair(false);
                    }
                    wg_wait<0>();
                    pin(acc0); pin(acc1);
                    if (lane < 2) asm volatile("mbarrier.arrive.shared::cluster.b64 _, [%0];" ::"r"(rel + 16 * xprev + 8) : "memory");
                    const uint32_t wst = sb + (br == 0 ? OFF_R : 0) + warp * 768 + (lane & 7) * 16;
                    const uint32_t a0 = wst + (lane >> 3) * 128;
                    const uint32_t a1 = wst + (lane < 16 ? 512 + (lane >> 3) * 128 : 6144 + ((lane >> 3) - 2) * 128);
                    const uint32_t a2 = wst + 6144 + 256 + (lane >> 3) * 128;
                    const bool poly = (POLY16 >> ((mt * 8 + warp) & 15)) & 1;
                    const uint32_t augq = br ? 0u : (t & 1) ? 0x00003D2Du : 0x3F8043C0u;
                    const uint32_t augk = br ? 0u : (t & 1) ? (poly ? 0u : 0x00003F80u) : (poly ? 0x00003F80u : 0x3F800000u);
                    const uint32_t augv = (t & 1) ? 0u : 0x00003F80u;
                    const float sc2 = br ? 0.5f * QSCALE : QSCALE;
                    {
                        auto ACC = [&](int u, int j, int e) -> float& {
                            const int grp = !G ? 5 * u + j : (u & 1) ? (u >> 1) * 8 + 3 + j : j < 2 ? 24 + u + j : (u >> 1) * 8 + j - 2;
                            const int i = grp * 4 + e;
                            return i < N0 ? acc0[i % N0] : acc1[(i - N0 + 120 - N0) % (120 - N0)];
                        };
                        if (G ? ct == 6 : ct < 2) {
#pragma unroll
                            for (int i = 0; i < (G ? 80 : 120); i++) ACC(i / 20, i / 4 % 5, i % 4) *= i / 4 % 5 == 2 ? sc2 : QSCALE;
                        }
                        if (br == 1) named_sync(1, 256);
                        else mbar_wait(bars + B_HDR, 0);
#pragma unroll
                        for (int u = 0; u < 6; u++) {
                            uint32_t v[2][5];
#pragma unroll
                            for (int j = 0; j < 10; j++) v[j / 5][j % 5] = pack2(ACC(u, j % 5, 2 * (j / 5)), ACC(u, j % 5, 2 * (j / 5) + 1));
                            const int blk = G ? (ct - 6) * 3 + (u >> 1) : ct;
                            const uint32_t aug = blk < 2 ? augq : blk < 4 ? augk : augv;
                            stsm4(a0 + u * 12288, v[0][0], v[0][1], t < 2 ? v[0][2] : aug, v[1][0]);
                            stsm4(a1 + u * 12288, v[1][1], t < 2 ? v[1][2] : aug, v[0][3], v[0][4]);
                            stsm4(a2 + u * 12288, t < 2 ? aug : v[0][2], v[1][3], v[1][4], t < 2 ? aug : v[1][2]);
                        }
                    }
                };
                if (ct < 6) tile(Bool<false>()); else tile(Bool<true>());
                fence_async_smem();
                __syncwarp();
                if (lane == 0) mbar_arrive(bars + (br ? B_STGA : wg ? B_STG1 : B_STGB));
            }
            asm volatile("setmaxnreg.dec.sync.aligned.u32 128;");
        } else if (warp < 12) {
            asm volatile("setmaxnreg.dec.sync.aligned.u32 80;");
            if (warp != 9) {
                if (warp == 11) {
                    uint32_t xs = 0, ph = 0;
#pragma unroll
                    for (int i = 1; i < 3; i++) {
                        while (clock_lo() - t_start < (i == 1 ? G1 : G2)) {}
                        if (elect_one()) tma_x(sb + OFF_X + i * 16384, &tmX, i * 64, mt * 8, bars + B_FULL + 16 * i);
                    }
#pragma unroll 1
                    for (int P = 3; P < 20; P++) {
                        const int k0 = (P < 10 ? P : P - 13) * 64;
                        mbar_wait(bars + B_EMPTY + 16 * xs + 8, ph);
                        if (elect_one()) {
                            if (k0 >= 0) tma_x(sb + OFF_X + xs * 16384, &tmX, k0, mt * 8, bars + B_FULL + 16 * xs);
                            if (P == 7) { prefetch_tmap(&tmWa); prefetch_tmap(&tmGa); prefetch_tmap(&tmS); }
                        }
                        if (++xs == 3) { xs = 0; ph ^= 1; }
                    }
                } else {
                    const int at = (bid & 1) * 2 + (warp == 10);
                    WBox bx = w_box(&tmWb, &tmGb, nt, at);
                    uint32_t s = 0, ph = 0;
#pragma unroll
                    for (int i = 2; i < 6; i++) {
                        while (clock_lo() - t_start < (i < 4 ? G1 : G2)) {}
                        if (elect_one()) tma_3d_mc(sb + i * 16384 + at * 4096, bx.tm, bx.c0, i * 32, bx.c1, bars + B_FULL + 8 * i, 3);
                    }
#pragma unroll 1
                    for (int it = 6; it < 40; it++) {
                        const int k0 = (it < 20 ? it : it < 26 ? it - 6 : it - 26) * 32;
                        if (it == 20) bx = w_box(&tmWa, &tmGa, p1_nta(nt), at);
                        const int bytes = ((s & 1) || (it >= 20 && it < 26)) ? 16384 : 32768;
                        mbar_wait(bars + B_EMPTY + 8 * s, ph);
                        if (elect_one()) {
                            tma_3d_mc(sb + s * 16384 + at * 4096, bx.tm, bx.c0, k0, bx.c1, bars + B_FULL + 8 * s, 3);
                            if (warp == 8) mbar_expect_tx(bars + B_FULL + 8 * s, bytes);
                        }
                        if (++s == 6) { s = 0; ph ^= 1; }
                    }
                }
                mbar_wait(bars + B_KV, 0);
                if (warp == 11) {
                    if (elect_one()) {
                        load_kv(sb, h, 1, 4, 4, 6);
                        bulk_g2s(sb + OFF_R + 12288, g_qkv + (size_t)h * HEAD_BYTES + qb * 24576 + 12288, 12288, bars + B_KV + 8);
                    }
                } else {
                    mbar_wait(bars + B_EMPTY + 24, 0);
                    if (elect_one()) { if (warp == 8) load_kv(sb, h, 2, 8, 1, 12); else load_kv(sb, h, 2, 9, 11, 0); }
                }
            } else {
                mbar_wait(bars + B_STGB, 0);
                uint32_t tick = clock_lo() - PACE;
#pragma unroll 1
                for (int i = 0; i < 24; i++) {
                    const int hs = i < 12 ? i : i - 12, half = i < 12 ? 0 : 3072;
                    uint8_t* dst = g_qkv + (tile_slot(nt, hs) * (uint32_t)HEAD_BYTES + mt * 6144 + half);
                    if (i == 12) mbar_wait(bars + B_STG1, 0);
                    while (__shfl_sync(0xffffffffu, clock_lo() - tick, 0) < PACE) {}
                    tick += PACE;
                    if (elect_one()) bulk_s2g(dst, sb + OFF_R + hs * 6144 + half, 3072);
                }
                if (elect_one()) {
                    mbar_wait(bars + B_NRM, 0);
                    bulk_s2g(g_nrm + mt * 96 + nt * 12, bars + B_MISC, 48);
                    bulk_commit();
                    bulk_wait_all();
                    flag_add_done(g_flag + (F_QKVB + nt) * 32);
                    flag_wait_head(g_flag + F_QKVB * 32, h, 128);
                    fence_async_smem();
                    load_kv(sb, h, 0, 0, 4, 6);
                    bulk_g2s(sb + OFF_R, g_qkv + (size_t)h * HEAD_BYTES + qb * 24576, 12288, bars + B_KV);
                }
                __syncwarp();
                {
                    const uint32_t w = ldcg_u32(g_nrm + (lane < 16 ? lane * 96 + slot_index(32 + h) : (qb * 4 + (lane & 3)) * 96 + slot_index(h)));
                    const float kn = __uint_as_float(__reduce_max_sync(0xffffffffu, lane < 16 ? w : 0u));
                    if (lane >= 16 && lane < 20) s_misc[lane] = __uint_as_float(w) * kn <= SCORE_LIMIT2 ? 0.f : 1.f;
                    __syncwarp();
                    if (elect_one()) mbar_arrive(bars + B_KV + 24);
                }
            }
            __syncwarp();
            named_sync(5, 128);
            asm volatile("setmaxnreg.inc.sync.aligned.u32 128;");
        } else {
            mbar_wait(bars + B_FULL + 40, 0);
            {
                uint4 wv[7];
#pragma unroll
                for (int e = 0; e < 7; e++) {
                    const int i = threadIdx.x - 384 + e * 128, d = bid * 800 + i;
                    const int kr = d & 7, ng = (d >> 3) % 20, kg = (d / 160) % 80, part = bid >> 4;
                    const int k = (kg < 40 ? kg : kg + 40) * 8 + (part & 1) * 320 + kr;
                    const uint8_t* src = (k < 640 ? woa + k * 1280 : wob + (k - 640) * 1280) + ((part >> 1) * 20 + ng) * 16;
                    if (i < 800) wv[e] = __ldg(reinterpret_cast<const uint4*>(src));
                }
                const uint2* gw = reinterpret_cast<const uint2*>(gate_w) + lane;
                const uint2* xr = reinterpret_cast<const uint2*>(x + (size_t)(bid * 16 + (warp - 12) * 4) * DM) + lane;
                uint2 gv[5], xv[4][5];
#pragma unroll
                for (int i = 0; i < 5; i++) gv[i] = __ldg(gw + 32 * i);
#pragma unroll
                for (int i = 0; i < 20; i++) xv[i / 5][i % 5] = __ldg(xr + 32 * i);
                float a[4];
#pragma unroll
                for (int e = 0; e < 4; e++) {
                    a[e] = 0.f;
#pragma unroll
                    for (int i = 0; i < 5; i++) {
                        a[e] = fmaf(bf_lo(xv[e][i].x), bf_lo(gv[i].x), a[e]); a[e] = fmaf(bf_hi(xv[e][i].x), bf_hi(gv[i].x), a[e]);
                        a[e] = fmaf(bf_lo(xv[e][i].y), bf_lo(gv[i].y), a[e]); a[e] = fmaf(bf_hi(xv[e][i].y), bf_hi(gv[i].y), a[e]);
                    }
                }
#pragma unroll
                for (int o = 16; o; o >>= 1) {
#pragma unroll
                    for (int e = 0; e < 4; e++) a[e] += __shfl_xor_sync(0xffffffffu, a[e], o);
                }
                const float z = lane == 0 ? a[0] : lane == 1 ? a[1] : lane == 2 ? a[2] : a[3];
                if (lane < 4) asm volatile("st.shared.f32 [%0], %1;" ::"r"(sb + OFF_R + 12800 + ((lane & 1) * 8 + (warp - 12) * 2 + (lane >> 1)) * 4), "f"(__fdividef(1.f, 1.f + __expf(-z))) : "memory");
#pragma unroll
                for (int e = 0; e < 7; e++) {
                    const int i = threadIdx.x - 384 + e * 128;
                    if (i < 800) asm volatile("st.shared.v4.b32 [%0], {%1,%2,%3,%4};" ::"r"(sb + OFF_R + i * 16), "r"(wv[e].x), "r"(wv[e].y), "r"(wv[e].z), "r"(wv[e].w) : "memory");
                }
                fence_async_smem();
                __syncwarp();
                if (lane == 0) mbar_arrive(bars + B_HLP);
                if (warp == 15 && elect_one()) {
                    mbar_wait(bars + B_HLP, 0);
                    bulk_s2g(g_wo + bid * 800, sb + OFF_R, 12800);
                    bulk_s2g(g_gate + bid * 16, sb + OFF_R + 12800, 64);
                    bulk_commit();
                    bulk_wait_all();
                    mbar_arrive(bars + B_HDR);
                    flag_add_done(g_flag + F_HELP * 32);
                }
                __syncwarp();
            }
            mbar_wait(bars + B_STGB, 0); mbar_wait(bars + B_STG1, 0);
#pragma unroll 1
            for (int hs = warp - 12; hs < 12; hs += 4) {
                uint32_t nm = 0;
                if (tile_slot(nt, hs) < 64) {
#pragma unroll
                    for (int i = 0; i < 4; i++) {
                        const uint32_t a = sb + OFF_R + hs * 6144 + (i * 4 + (lane >> 3)) * 384 + (lane & 7) * 16;
                        const uint4 k0 = lds128(a), k1 = lds128(a + 128);
                        uint32_t k2, k3;
                        asm volatile("ld.shared.v2.b32 {%0,%1}, [%2];" : "=r"(k2), "=r"(k3) : "r"(a + 256 + (hs & 1) * 8));
                        uint32_t n0 = hfma2(k2, k2, 0u), n1 = hfma2(k3, k3, 0u);
                        n0 = hfma2(k0.x, k0.x, n0); n1 = hfma2(k0.y, k0.y, n1); n0 = hfma2(k0.z, k0.z, n0); n1 = hfma2(k0.w, k0.w, n1);
                        n0 = hfma2(k1.x, k1.x, n0); n1 = hfma2(k1.y, k1.y, n1); n0 = hfma2(k1.z, k1.z, n0); n1 = hfma2(k1.w, k1.w, n1);
                        nm = max(nm, __float_as_uint((bf_lo(n0) + bf_hi(n0)) + (bf_lo(n1) + bf_hi(n1))));
                    }
                }
                nm = __reduce_max_sync(0xffffffffu, nm);
                if (lane == 0) s_misc[hs] = __uint_as_float(nm) * 1.03f;
            }
            fence_async_smem();
            __syncwarp();
            if (lane == 0) mbar_arrive(bars + B_NRM);
        }
    }

    uint32_t aflag;
    {
        const uint64_t dK0 = mkdesc(sb, 128, 384, 0), dK1 = mkdesc(sb + 256, 0, 384, 0), dV = mkdesc(sb, 384, 128, 0);
        const int wid = fresh_wid();
        mbar_wait(bars + B_KV, 0);
#pragma unroll 1
        for (int u = 0; u < 2; u++) {
            uint32_t q[8];
            {
                const uint32_t a = sb + OFF_R + (u * 32 + here(wid) * 2) * 384 + (fresh_tid() & 31) * 4;
                q[0] = lds32(a); q[1] = lds32(a + 384); q[2] = lds32(a + 128); q[3] = lds32(a + 512);
                q[4] = lds32(a + 256); q[5] = lds32(a + 640);
                q[6] = lds32(bars + B_ZERO); q[7] = lds32(bars + B_ZERO + 4);
            }
            float o[12];
#pragma unroll
            for (int i = 0; i < 12; i++) o[i] = 0.f;
            pin(o); pin(q);
            float s0[32], s1[32];
            uint32_t p[16];
            float g0, g1;
            wg_fence(); qk_tile(s0, q, dK0 + (k_off(0) >> 4), dK1 + (k_off(0) >> 4)); wg_commit();
#pragma unroll
            for (int j = 0; j < 32; j += 2) {
                qk_tile(s1, q, dK0 + (k_off(j + 1) >> 4), dK1 + (k_off(j + 1) >> 4)); wg_commit();
                wg_wait<1>(); pin(s0);
                exp_pv_tile(s0, p, o, dV + (v_off(j) >> 4), POLY16 >> (4 * (j & 3)));
                if (j == 2 || j == 6 || j == 18) { mbar_wait(bars + B_KV + (j == 2 ? 8 : j == 6 ? 16 : 24), 0); wg_fence(); }
                const bool ahead = j + 2 < 32 && j != LJ;
                if (ahead) { qk_tile(s0, q, dK0 + (k_off(j + 2) >> 4), dK1 + (k_off(j + 2) >> 4)); wg_commit(); }
                {
                    if (j == 10) { if (u == 1 && elect_one()) mbar_arrive(bars + B_RET); }
                    if (j == 4) {
                        if (u == 0 && wid == 14 && elect_one()) {
                            const int bid = fresh_bid();
                            mbar_wait(bars + B_STGA, 0);
#pragma unroll
                            for (int i = 0; i < 3; i++) tma_store_3d(&tmS, sb + i * SLOT, 0, (p1_mp(bid) * 2 + (bid & 1)) * 16, 96 + tile_slot(p1_nta(p1_nt(bid)), i * 4));
                            bulk_commit();
                        }
                        __syncwarp();
                    }
                    if (j == 12) {
                        if (u == 0 && wid == 14 && elect_one()) service(sb, 0, 0);
                        __syncwarp();
                    }
                    if (j == 10) { if (u == 1 && wid == 9 && elect_one()) service(sb, 1, 0); __syncwarp(); }
                    if (j == 20 || j == 26) { if (u == 1 && elect_one()) mbar_arrive(bars + (j == 20 ? B_RET + 24 : B_R26)); }
                    if (j == 18) { if (u == 1 && wid == 5 && elect_one()) service(sb, 4, 0); __syncwarp(); }
                    if (j == 22) { if (u == 1 && wid == 14 && elect_one()) service(sb, 3, 0); __syncwarp(); }
                    if (j == 28) { if (u == 1 && wid == 10 && elect_one()) service(sb, 2, aflag); __syncwarp(); }
                    if (j == 26) {
                        const float* gp = g_gate + (uint32_t)((fresh_bid() & 3) * 512 + u * 256 + here(wid) * 16) + (((uint32_t)fresh_tid() & 31) >> 2);
                        g0 = ldcg_f32(gp); g1 = ldcg_f32(gp + 8);
                        const int b2 = fresh_bid();
                        aflag = ld_relaxed(u ? atta_in(b2) : g_flag + (F_QKVA + slot_tile(min(fresh_tid() & 31, 2) * 32 + (b2 >> 2))) * 32);
                    }
                }
                if (ahead) wg_wait<1>(); else wg_wait<0>();
                pin(s1);
                exp_pv_tile(s1, p, o, dV + (v_off(j + 1) >> 4), POLY16 >> (4 * ((j + 1) & 3)));
                if (j == LJ) {
                    wg_wait<0>();
                    if (u == 1) local_attn(sb, here(wid), dK0, dK1, dV);
                    wg_fence(); qk_tile(s0, q, dK0 + (k_off(j + 2) >> 4), dK1 + (k_off(j + 2) >> 4)); wg_commit();
                }
            }
            const int tid = fresh_tid(), lane = tid & 31, warp = here(wid);
            const int bid = fresh_bid(), h = bid >> 2, qb = bid & 3;
            if (u == 0 && wid == 13) {
                if (__all_sync(0xffffffffu, aflag >= 16)) asm volatile("fence.acquire.gpu;" ::: "memory");
                else if (elect_one()) flag_wait_head(g_flag + F_QKVA * 32, h, 0);
                __syncwarp();
            }
            wg_wait<0>(); pin(o);
            if (u == 1 && lane == 0) mbar_arrive(bars + B_RET + 16);
            float l0, l1;
            uint32_t w[6];
            finish_o(o, w, h & 1, 1.f - g0, 1.f - g1, lane, l0, l1);
            store_o(w, out_ptr(qb * 32 + u * 16 + warp, h, 80, lane), 0);
            const float sum = (((o[0] + o[1]) + (o[2] + o[3])) + ((o[4] + o[5]) + (o[6] + o[7]))) + ((o[8] + o[9]) + (o[10] + o[11]));
            if (__any_sync(0xffffffffu, !(fminf(l0, l1) >= 0x1p-30f && fmaxf(l0, l1) <= 0x1p100f && fabsf(sum) <= 1e37f && s_misc[16 + u * 2 + (warp >> 3)] == 0.f)))
                exact_rows(h, qb * 32 + u * 16 + warp, lane);
        }
        __syncwarp();
        if (elect_one()) mbar_arrive(bars + B_PUB + (wid >> 2) * 8);
    }

    {
        const int tid = fresh_tid(), lane = tid & 31;
        const int warp = __shfl_sync(0xffffffffu, tid >> 5, 0);
        const int bid = fresh_bid(), rank = bid & 1;
        if (warp >= 8) {
            asm volatile("setmaxnreg.dec.sync.aligned.u32 40;");
            if ((warp == 8 || warp == 12 || warp >= 14) && elect_one()) {
                const int wg = warp == 15 ? 0 : warp == 14 ? 1 : warp >> 2;
                mbar_wait(bars + B_PUB + 8 * wg, 0);
                flag_add_done(attb_out(bid, wg));
            }
            if (warp == 13 && elect_one()) {
#pragma unroll
                for (int i = 0; i < 3; i++) { mbar_wait(bars + B_W0 + 8 * (i ? i : 1), 0); load_wo(sb, 7 + i, 1); }
            }
            if (warp == 10 && elect_one()) {
                if (aflag < 16) flag_wait(atta_in(bid), 16);
                mbar_wait(bars + B_RET + 16, 0);
                if (aflag < 16) { load_frag(sb, bid, 0, 0); load_frag(sb, bid, 1, 0); }
                mbar_wait(bars + B_W0, 0);
                load_frag(sb, bid, 0, 1);
                mbar_wait(bars + B_W0 + 8, 0);
                load_frag(sb, bid, 0, 2);
            }
            if (warp == 11 && elect_one()) {
                mbar_wait(bars + B_AE, 0);
                fence_async_smem();
                flag_wait_fast(attb_in(bid), 16);
                load_frag(sb, bid, 1, 1); load_frag(sb, bid, 1, 2);
                if (atomicAdd(g_flag + F_EXIT * 32, 1u) == 127u) {
#pragma unroll 1
                    for (int i = 0; i < F_COUNT; i++) g_flag[i * 32] = 0u;
                }
            }
        } else {
            const int mh = warp >> 2;
            const int mt64 = (bid >> 5) * 8 + mh * 4 + ((bid >> 3) & 3);
            const int pos = frag_pos(warp & 3, lane);
            const uint2* ap = g_att + (mt64 * 160 + rank * 40) * 128 + pos;
            const uint32_t as0 = sb + frag_off(mh, 0) + pos * 8, as1 = sb + frag_off(mh, 5) + pos * 8, as9 = sb + frag_off(mh, 9) + pos * 8, fb = bars + B_AF + mh * 32;
            const uint64_t db = mkdesc(SB0, 2560, 128, 0);
            uint32_t a[6][16];
            auto ldg = [&](int i) {
#pragma unroll
                for (int j = 0; j < 8; j++)
                    asm volatile("ld.global.L1::no_allocate.v2.b32 {%0, %1}, [%2];" : "=r"(a[i % 6][2 * j]), "=r"(a[i % 6][2 * j + 1])
                                 : "l"(ap + ((i / 5) * 80 + (i % 5) * 8 + j) * 128) : "memory");
            };
            auto lds = [&](int i) {
                if (i == 0 || i == 5 || i == 7) mbar_wait(fb + (i / 3) * 8, 0);
#pragma unroll
                for (int j = 0; j < 8; j++)
                    asm volatile("ld.shared.v2.b32 {%0, %1}, [%2];" : "=r"(a[i % 6][2 * j]), "=r"(a[i % 6][2 * j + 1])
                                 : "r"(i == 9 ? as9 + j * 1024 : (i < 5 ? as0 : as1) + ((i % 5) * 8 + j) * 1024) : "memory");
            };
            float snd[40], keep[40];
            const uint64_t dk = db + rank * 80, ds = db + (rank ^ 1) * 80;
            auto half = [&](float (&acc)[40], uint64_t d, int i) {
#pragma unroll
                for (int k = 0; k < 4; k++)
                    if (i + k == 0) wgmma_rs80f(acc, a[0][0], a[0][1], a[0][2], a[0][3], d + (wo_off(0) >> 4));
                    else wgmma_rs80(acc, a[i % 6][4 * k], a[i % 6][4 * k + 1], a[i % 6][4 * k + 2], a[i % 6][4 * k + 3], d + (wo_off(i) >> 4) + k * 320);
            };
            auto mma = [&](int i) {
                if (i == 0 || wo_bar(i) != wo_bar(i - 1)) mbar_wait(bars + B_WO + 8 * wo_bar(i), 0);
                pin(a[i % 6]);
                wg_fence();
                half(snd, ds, i);
                half(keep, dk, i);
                wg_commit();
            };
            lds(0); mma(0);
            wg_wait<0>();
            lds(1); mma(1);
            asm volatile("setmaxnreg.inc.sync.aligned.u32 216;");
            ldg(2); ldg(3);
            if (lane == 0) mbar_arrive(bars + B_AE);
            ldg(4);
#pragma unroll
            for (int i = 0; i < 3; i++) {
                wg_wait<1>();
                if (lane == 0) mbar_arrive(bars + B_W0 + 8 * i);
                mma(i + 2);
            }
            wg_wait<0>();
            if (lane == 0) mbar_arrive_cluster(bars + B_RET + 8, rank ^ 1);
            lds(5); lds(6);
            pin(a[5]); pin(a[0]);
            wg_fence(); half(snd, ds, 5); half(snd, ds, 6);
            half(keep, dk, 5);
            lds(7); lds(8); lds(9);
            pin(a[1]); pin(a[2]); pin(a[3]);
#pragma unroll
            for (int i = 7; i < 10; i++) { mbar_wait(bars + B_WO + 8 * wo_bar(i), 0); wg_fence(); half(snd, ds, i); }
            wg_commit();
#pragma unroll
            for (int i = 6; i < 10; i++) half(keep, dk, i);
            wg_commit();
            const uint32_t xs = sb + (mh ? wo_off(4) : wo_off(3)) + (tid & 127) * 16;
            {
                uint32_t ra, rb;
                asm volatile("mapa.shared::cluster.u32 %0, %1, %2;" : "=r"(ra) : "r"(xs), "r"(rank ^ 1));
                asm volatile("mapa.shared::cluster.u32 %0, %1, %2;" : "=r"(rb) : "r"(bars + B_XCH + 8 * mh), "r"(rank ^ 1));
                mbar_wait(bars + B_RET + 8, 0);
                wg_wait<1>();
                pin(snd);
#pragma unroll
                for (int j = 0; j < 5; j++)
                    asm volatile("st.async.weak.shared::cluster.mbarrier::complete_tx::bytes.v4.b32 [%0], {%1,%2,%3,%4}, [%5];"
                                 ::"r"(ra + j * 2048), "r"(pack2(snd[8 * j], snd[8 * j + 1])), "r"(pack2(snd[8 * j + 2], snd[8 * j + 3])),
                                   "r"(pack2(snd[8 * j + 4], snd[8 * j + 5])), "r"(pack2(snd[8 * j + 6], snd[8 * j + 7])), "r"(rb) : "memory");
            }
            named_sync(8 + mh, 128);
            mbar_wait(bars + B_XCH + 8 * mh, 0);
            uint4 rcv[10];
#pragma unroll
            for (int j = 0; j < 5; j++) {
                const uint4 v = lds128(xs + j * 2048);
                rcv[2 * j] = make_uint4(v.x << 16, v.x & 0xffff0000u, v.y << 16, v.y & 0xffff0000u);
                rcv[2 * j + 1] = make_uint4(v.z << 16, v.z & 0xffff0000u, v.w << 16, v.w & 0xffff0000u);
            }
            wg_wait<0>();
            pin(keep);
            uint32_t w[20];
#pragma unroll
            for (int j = 0; j < 10; j++) {
                const uint4 o = rcv[j];
                w[2 * j] = pack2(keep[4 * j] + __uint_as_float(o.x), keep[4 * j + 1] + __uint_as_float(o.y));
                w[2 * j + 1] = pack2(keep[4 * j + 2] + __uint_as_float(o.z), keep[4 * j + 3] + __uint_as_float(o.w));
            }
            const uint32_t ot = sb + frag_off(mh, 5) + (warp & 3) * 2816;
            const uint32_t sa = ot + (lane & 15) * 176 + (lane >> 4) * 16;
#pragma unroll
            for (int j = 0; j < 5; j++) stsm4(sa + j * 32, w[4 * j], w[4 * j + 1], w[4 * j + 2], w[4 * j + 3]);
            __syncwarp();
            __nv_bfloat16* ob = out + (size_t)(mt64 * 64 + (warp & 3) * 16) * DM + (bid & 7) * 80;
#pragma unroll
            for (int i = 0; i < 5; i++) {
                const int c = lane + 32 * i, r = c / 10;
                stg128(ob + ((r & 7) * 2 + (r >> 3)) * DM + (c % 10) * 8, lds128(ot + r * 176 + (c % 10) * 16));
            }
        }
    }
}

typedef CUresult (*EncodeFn)(CUtensorMap*, CUtensorMapDataType, cuuint32_t, void*, const cuuint64_t*, const cuuint64_t*,
                             const cuuint32_t*, const cuuint32_t*, CUtensorMapInterleave, CUtensorMapSwizzle,
                             CUtensorMapL2promotion, CUtensorMapFloatOOBfill);

void make_map(EncodeFn fn, CUtensorMap* tm, const void* ptr, int rank, const cuuint64_t* dims, const cuuint64_t* strides,
              const cuuint32_t* box, CUtensorMapSwizzle swz) {
    const cuuint32_t es[4] = {1, 1, 1, 1};
    fn(tm, CU_TENSOR_MAP_DATA_TYPE_BFLOAT16, rank, const_cast<void*>(ptr), dims, strides, box, es, CU_TENSOR_MAP_INTERLEAVE_NONE,
       swz, CU_TENSOR_MAP_L2_PROMOTION_L2_256B, CU_TENSOR_MAP_FLOAT_OOB_FILL_NONE);
}

}

extern "C" void kernel_launch(void* const* d_in, const int* in_sizes, int n_in, void* d_out, int out_size) {
    (void)in_sizes; (void)n_in; (void)out_size;
    const __nv_bfloat16* x = (const __nv_bfloat16*)d_in[0];
    const __nv_bfloat16* wqkv_a = (const __nv_bfloat16*)d_in[1];
    const __nv_bfloat16* wo_a = (const __nv_bfloat16*)d_in[2];
    const __nv_bfloat16* wqkv_b = (const __nv_bfloat16*)d_in[4];
    const __nv_bfloat16* wo_b = (const __nv_bfloat16*)d_in[5];
    const __nv_bfloat16* gate_w = (const __nv_bfloat16*)d_in[6];

    void* fnp = nullptr;
    cudaDriverEntryPointQueryResult qr;
    cudaGetDriverEntryPoint("cuTensorMapEncodeTiled", &fnp, cudaEnableDefault, &qr);
    EncodeFn enc = (EncodeFn)fnp;
    void* qkv = nullptr;
    cudaGetSymbolAddress(&qkv, g_qkv);

    CUtensorMap tmX, tmWb, tmWa, tmGb, tmGa, tmS;
    {
        const cuuint64_t d[4] = {640, 8, 2, 128}, s[3] = {2560, 1280, 20480};
        const cuuint32_t b[4] = {64, 8, 2, 8};
        make_map(enc, &tmX, x, 4, d, s, b, CU_TENSOR_MAP_SWIZZLE_128B);
    }
    {
        const cuuint64_t d[3] = {320, 640, 6}, dg[3] = {16, 640, 6}, s[2] = {3840, 640};
        const cuuint32_t b[3] = {64, 32, 1}, bg[3] = {16, 32, 4};
        make_map(enc, &tmWb, wqkv_b, 3, d, s, b, CU_TENSOR_MAP_SWIZZLE_128B);
        make_map(enc, &tmWa, wqkv_a, 3, d, s, b, CU_TENSOR_MAP_SWIZZLE_128B);
        make_map(enc, &tmGb, wqkv_b + 240, 3, dg, s, bg, CU_TENSOR_MAP_SWIZZLE_32B);
        make_map(enc, &tmGa, wqkv_a + 240, 3, dg, s, bg, CU_TENSOR_MAP_SWIZZLE_32B);
    }
    {
        const cuuint64_t d[3] = {192, 256, 192}, s[2] = {384, (cuuint64_t)HEAD_BYTES};
        const cuuint32_t b[3] = {192, 16, 4};
        make_map(enc, &tmS, qkv, 3, d, s, b, CU_TENSOR_MAP_SWIZZLE_NONE);
    }
    cudaFuncSetAttribute(k_fused, cudaFuncAttributeMaxDynamicSharedMemorySize, SMEM_BYTES);
    k_fused<<<128, 512, SMEM_BYTES, cudaStreamPerThread>>>(tmX, tmWb, tmWa, tmGb, tmGa, tmS, x, gate_w, (const uint8_t*)wqkv_b,
                                                          (const uint8_t*)wo_a, (const uint8_t*)wo_b, (__nv_bfloat16*)d_out);
}
```

```cpp
#include <cuda_runtime.h>
#include <cuda_bf16.h>
#include <cuda.h>
#include <stdint.h>

namespace {

constexpr int SEQ = 2048, DM = 640;
constexpr int HEAD_BYTES = 256 * 384;
#define POLYM 0xddddu
constexpr uint32_t POLY16 = POLYM;
constexpr float QSCALE = 0.22360679774997896f * 1.4426950408889634f;

__device__ __align__(1024) uint8_t g_qkv[2 * 96 * HEAD_BYTES];
__device__ __align__(128) float g_gate[SEQ];
__device__ __align__(128) float g_nrm[16 * 96];
enum { F_QKVB = 0, F_QKVA = 8, F_HELP = 16, F_EXIT = 17, F_ATTA = 18, F_ATTB = 26, F_COUNT = 58 };
__device__ uint32_t g_flag[F_COUNT * 32];
__device__ __align__(1024) uint4 g_wo[8 * 160 * 10 * 8];
__device__ __align__(1024) uint2 g_att[32 * 160 * 128];

#define TR(i, cond)
#define TRINIT()
#define TRFLUSH()
#define TR2(i, c) TR(i, c)
__device__ __forceinline__ uint32_t slot_tile(uint32_t hs) { return (hs & 15) < 12 ? hs >> 4 : hs < 48 ? 6 : 7; }
__device__ __forceinline__ uint32_t slot_index(uint32_t hs) { return (hs & 15) < 12 ? (hs >> 4) * 12 + (hs & 15) : 72 + (hs >> 4) * 4 + (hs & 3); }
__device__ __forceinline__ uint32_t tile_slot(uint32_t t, uint32_t i) { return t < 6 ? t * 16 + i : ((t - 6) * 3 + (i >> 2)) * 16 + 12 + (i & 3); }

__device__ __forceinline__ uint32_t smem_u32(const void* p) { return (uint32_t)__cvta_generic_to_shared(p); }
__device__ __forceinline__ void mbar_init(uint32_t bar, int cnt) { asm volatile("mbarrier.init.shared::cta.b64 [%0], %1;" ::"r"(bar), "r"(cnt) : "memory"); }
__device__ __forceinline__ void mbar_expect_tx(uint32_t bar, int bytes) { asm volatile("mbarrier.arrive.expect_tx.shared::cta.b64 _, [%0], %1;" ::"r"(bar), "r"(bytes) : "memory"); }
__device__ __forceinline__ void mbar_arrive(uint32_t bar) { asm volatile("mbarrier.arrive.shared::cta.b64 _, [%0];" ::"r"(bar) : "memory"); }
__device__ __forceinline__ bool mbar_try(uint32_t bar, uint32_t parity) {
    uint32_t ok;
    asm volatile("{\n.reg .pred p;\nmbarrier.try_wait.parity.shared::cta.b64 p, [%1], %2;\nselp.u32 %0, 1, 0, p;\n}\n" : "=r"(ok) : "r"(bar), "r"(parity) : "memory");
    return ok;
}
__device__ __forceinline__ void mbar_wait(uint32_t bar, uint32_t parity) {
    if (mbar_try(bar, parity)) return;
#pragma unroll 1
    for (int i = 0; i < (1 << 21); i++)
        if (mbar_try(bar, parity)) return;
    __trap();
}
__device__ __forceinline__ void fence_mbar_init() { asm volatile("fence.mbarrier_init.release.cluster;" ::: "memory"); }
__device__ __forceinline__ void tma_x(uint32_t dst, const CUtensorMap* tm, int k, int blk16, uint32_t bar) {
    asm volatile("cp.async.bulk.tensor.4d.shared::cluster.global.mbarrier::complete_tx::bytes [%0], [%1, {%2, %5, %5, %3}], [%4];"
                 ::"r"(dst), "l"(tm), "r"(k), "r"(blk16), "r"(bar), "r"(0) : "memory");
}
__device__ __forceinline__ void tma_3d_mc(uint32_t dst, const CUtensorMap* tm, int c0, int c1, int c2, uint32_t bar, uint16_t mask) {
    asm volatile("cp.async.bulk.tensor.3d.shared::cluster.global.mbarrier::complete_tx::bytes.multicast::cluster [%0], [%1, {%2, %3, %4}], [%5], %6;"
                 ::"r"(dst), "l"(tm), "r"(c0), "r"(c1), "r"(c2), "r"(bar), "h"(mask) : "memory");
}
__device__ __forceinline__ void mbar_arrive_cluster(uint32_t bar, uint32_t cta) {
    asm volatile("{\n.reg .b32 ra;\nmapa.shared::cluster.u32 ra, %0, %1;\nmbarrier.arrive.shared::cluster.b64 _, [ra];\n}\n" ::"r"(bar), "r"(cta) : "memory");
}
__device__ __forceinline__ void tma_store_3d(const CUtensorMap* tm, uint32_t src, int c0, int c1, int c2) {
    asm volatile("cp.async.bulk.tensor.3d.global.shared::cta.bulk_group [%0, {%2, %3, %4}], [%1];" ::"l"(tm), "r"(src), "r"(c0), "r"(c1), "r"(c2) : "memory");
}
__device__ __forceinline__ void cluster_arrive() { asm volatile("barrier.cluster.arrive.relaxed.aligned;" ::: "memory"); }
__device__ __forceinline__ void cluster_wait() { asm volatile("barrier.cluster.wait.aligned;" ::: "memory"); }
__device__ __forceinline__ void named_sync(int id, int n) { asm volatile("bar.sync %0, %1;" ::"r"(id), "r"(n) : "memory"); }
__device__ __forceinline__ void flag_add_done(uint32_t* p) {
    asm volatile("fence.proxy.async.global;\nred.release.gpu.global.add.u32 [%0], 1;" ::"l"(p) : "memory");
}
__device__ __forceinline__ void flag_wait(const uint32_t* p, uint32_t target) {
#pragma unroll 1
    for (int i = 0; i < (1 << 22); i++) {
        uint32_t v;
        asm volatile("ld.acquire.gpu.global.u32 %0, [%1];" : "=r"(v) : "l"(p) : "memory");
        if (v >= target) return;
        __nanosleep(20);
    }
    __trap();
}
__device__ __forceinline__ void flag_wait_fast(const uint32_t* p, uint32_t target) {
    uint32_t v0, v1, v2;
    asm volatile("ld.relaxed.gpu.global.u32 %0, [%1];" : "=r"(v0) : "l"(p) : "memory");
    __nanosleep(100);
    asm volatile("ld.relaxed.gpu.global.u32 %0, [%1];" : "=r"(v1) : "l"(p) : "memory");
    __nanosleep(100);
#pragma unroll 1
    for (int i = 0; i < (1 << 22); i++) {
        asm volatile("ld.relaxed.gpu.global.u32 %0, [%1];" : "=r"(v2) : "l"(p) : "memory");
        if (v0 >= target) break;
        asm volatile("ld.relaxed.gpu.global.u32 %0, [%1];" : "=r"(v0) : "l"(p) : "memory");
        if (v1 >= target) break;
        asm volatile("ld.relaxed.gpu.global.u32 %0, [%1];" : "=r"(v1) : "l"(p) : "memory");
        if (v2 >= target) break;
        if (i == (1 << 22) - 1) __trap();
    }
    asm volatile("fence.acquire.gpu;" ::: "memory");
}
__device__ __forceinline__ void flag_wait_head(const uint32_t* base, int h, uint32_t help_target) {
    const uint32_t *p0 = base + slot_tile(h) * 32, *p1 = base + slot_tile(32 + h) * 32, *p2 = base + slot_tile(64 + h) * 32;
    const uint32_t target = 16;
#pragma unroll 1
    for (int i = 0; i < (1 << 22); i++) {
        uint32_t v0, v1, v2, v3;
        asm volatile("ld.relaxed.gpu.global.u32 %0, [%1];" : "=r"(v3) : "l"(g_flag + F_HELP * 32) : "memory");
        asm volatile("ld.relaxed.gpu.global.u32 %0, [%1];" : "=r"(v0) : "l"(p0) : "memory");
        asm volatile("ld.relaxed.gpu.global.u32 %0, [%1];" : "=r"(v1) : "l"(p1) : "memory");
        asm volatile("ld.relaxed.gpu.global.u32 %0, [%1];" : "=r"(v2) : "l"(p2) : "memory");
        if (v0 >= target && v1 >= target && v2 >= target && v3 >= help_target) { asm volatile("fence.acquire.gpu;" ::: "memory"); return; }
        __nanosleep(40);
    }
    __trap();
}
__device__ __forceinline__ uint32_t ld_relaxed(const uint32_t* p) { uint32_t v; asm volatile("ld.relaxed.gpu.global.u32 %0, [%1];" : "=r"(v) : "l"(p) : "memory"); return v; }
__device__ __forceinline__ float ldcg_f32(const float* p) { float v; asm volatile("ld.global.cg.f32 %0, [%1];" : "=f"(v) : "l"(p) : "memory"); return v; }
__device__ __forceinline__ uint32_t ldcg_u32(const void* p) { uint32_t v; asm volatile("ld.global.cg.b32 %0, [%1];" : "=r"(v) : "l"(p) : "memory"); return v; }
__device__ __forceinline__ void bulk_g2s(uint32_t dst, const void* src, int bytes, uint32_t bar) {
    asm volatile("fence.proxy.async.global;\ncp.async.bulk.shared::cluster.global.mbarrier::complete_tx::bytes [%0], [%1], %2, [%3];"
                 ::"r"(dst), "l"(src), "r"(bytes), "r"(bar) : "memory");
}
__device__ __forceinline__ void bulk_s2g(void* dst, uint32_t src, int bytes) {
    asm volatile("cp.async.bulk.global.shared::cta.bulk_group [%0], [%1], %2;" ::"l"(dst), "r"(src), "r"(bytes) : "memory");
}
__device__ __forceinline__ void bulk_commit() { asm volatile("cp.async.bulk.commit_group;" ::: "memory"); }
__device__ __forceinline__ void bulk_wait_all() { asm volatile("cp.async.bulk.wait_group 0;" ::: "memory"); }
__device__ __forceinline__ void fence_async_smem() { asm volatile("fence.proxy.async.shared::cta;" ::: "memory"); }
__device__ __forceinline__ void stsm4(uint32_t a, uint32_t r0, uint32_t r1, uint32_t r2, uint32_t r3) {
    asm volatile("stmatrix.sync.aligned.m8n8.x4.shared.b16 [%0], {%1,%2,%3,%4};" ::"r"(a), "r"(r0), "r"(r1), "r"(r2), "r"(r3) : "memory");
}
__device__ __forceinline__ void prefetch_tmap(const CUtensorMap* tm) { asm volatile("prefetch.tensormap [%0];" ::"l"(tm) : "memory"); }
__device__ __forceinline__ void wg_fence() { asm volatile("wgmma.fence.sync.aligned;" ::: "memory"); }
__device__ __forceinline__ void wg_commit() { asm volatile("wgmma.commit_group.sync.aligned;" ::: "memory"); }
template <int N> __device__ __forceinline__ void wg_wait() { asm volatile("wgmma.wait_group.sync.aligned %0;" ::"n"(N) : "memory"); }
__host__ __device__ constexpr uint64_t mkdesc(uint32_t addr, uint32_t lbo, uint32_t sbo, uint32_t swz) {
    return (uint64_t)((addr & 0x3FFFF) >> 4) | ((uint64_t)(lbo >> 4) << 16) | ((uint64_t)(sbo >> 4) << 32) | ((uint64_t)swz << 62);
}
template <int N> __device__ __forceinline__ void pin(float (&r)[N]) {
#pragma unroll
    for (int i = 0; i < N; i++) asm volatile("" : "+f"(r[i])::"memory");
}
template <int N> __device__ __forceinline__ void pin(uint32_t (&r)[N]) {
#pragma unroll
    for (int i = 0; i < N; i++) asm volatile("" : "+r"(r[i])::"memory");
}
__device__ __forceinline__ float ex2(float x) { float y; asm("ex2.approx.ftz.f32 %0, %1;" : "=f"(y) : "f"(x)); return y; }
__device__ __forceinline__ uint32_t pack2(float lo, float hi) { uint32_t r; asm("cvt.rn.bf16x2.f32 %0, %1, %2;" : "=r"(r) : "f"(hi), "f"(lo)); return r; }
__device__ __forceinline__ uint32_t hfma2(uint32_t a, uint32_t b, uint32_t c) { uint32_t d; asm("fma.rn.bf16x2 %0, %1, %2, %3;" : "=r"(d) : "r"(a), "r"(b), "r"(c)); return d; }
__device__ __forceinline__ float bf_lo(uint32_t v) { return __uint_as_float(v << 16); }
__device__ __forceinline__ float bf_hi(uint32_t v) { return __uint_as_float(v & 0xffff0000u); }
__device__ __forceinline__ void mma16816(float (&c)[4], uint32_t a0, uint32_t a1, uint32_t a2, uint32_t a3, uint32_t b0, uint32_t b1) {
    asm volatile("mma.sync.aligned.m16n8k16.row.col.f32.bf16.bf16.f32 {%0,%1,%2,%3}, {%4,%5,%6,%7}, {%8,%9}, {%0,%1,%2,%3};"
                 : "+f"(c[0]), "+f"(c[1]), "+f"(c[2]), "+f"(c[3]) : "r"(a0), "r"(a1), "r"(a2), "r"(a3), "r"(b0), "r"(b1));
}
__device__ __forceinline__ void mma1688(float (&c)[4], uint32_t a0, uint32_t a1, uint32_t b0) {
    asm volatile("mma.sync.aligned.m16n8k8.row.col.f32.bf16.bf16.f32 {%0,%1,%2,%3}, {%4,%5}, {%6}, {%0,%1,%2,%3};"
                 : "+f"(c[0]), "+f"(c[1]), "+f"(c[2]), "+f"(c[3]) : "r"(a0), "r"(a1), "r"(b0));
}
__device__ __forceinline__ uint32_t movm_t(uint32_t a) { uint32_t d; asm volatile("movmatrix.sync.aligned.m8n8.trans.b16 %0, %1;" : "=r"(d) : "r"(a)); return d; }
__device__ __forceinline__ void stg128(void* p, uint4 v) { asm volatile("st.global.v4.b32 [%0], {%1,%2,%3,%4};" ::"l"(p), "r"(v.x), "r"(v.y), "r"(v.z), "r"(v.w) : "memory"); }
__device__ __forceinline__ void stg64(void* p, uint32_t a, uint32_t b) { asm volatile("st.global.v2.b32 [%0], {%1,%2};" ::"l"(p), "r"(a), "r"(b) : "memory"); }
__device__ __forceinline__ int frag_pos(int warp4, int lane) { return ((lane & 2) << 5) | (warp4 << 4) | ((lane >> 2) << 1) | (lane & 1); }
__device__ __forceinline__ bool elect_one() {
    uint32_t p;
    asm volatile("{\n.reg .pred p;\nelect.sync _|p, 0xffffffff;\nselp.u32 %0, 1, 0, p;\n}\n" : "=r"(p));
    return p;
}
__device__ __forceinline__ uint32_t clock_lo() { uint32_t v; asm volatile("mov.u32 %0, %%clock;" : "=r"(v)); return v; }
__device__ __forceinline__ int fresh_bid() { int v; asm volatile("mov.u32 %0, %%ctaid.x;" : "=r"(v)); return v; }
__device__ __forceinline__ int fresh_wid() { int v; asm volatile("mov.u32 %0, %%tid.x;" : "=r"(v)); return __shfl_sync(0xffffffffu, v >> 5, 0); }
__device__ __forceinline__ int here(int v) { asm volatile("" : "+r"(v)); return v; }
__device__ __forceinline__ int fresh_tid() { int v; asm volatile("mov.u32 %0, %%tid.x;" : "=r"(v)); return v; }
__device__ __forceinline__ uint32_t lds32(uint32_t a) { uint32_t v; asm volatile("ld.shared.b32 %0, [%1];" : "=r"(v) : "r"(a) : "memory"); return v; }
__device__ __forceinline__ uint4 lds128(uint32_t a) { uint4 v; asm volatile("ld.shared.v4.b32 {%0,%1,%2,%3}, [%4];" : "=r"(v.x), "=r"(v.y), "=r"(v.z), "=r"(v.w) : "r"(a)); return v; }

__device__ __forceinline__ void wgmma_ss(float (&d)[96], uint64_t da, uint64_t db) {
    asm volatile("{\n.reg .pred p;\nsetp.eq.b32 p, 0, 0;\n"
        "wgmma.mma_async.sync.aligned.m64n192k16.f32.bf16.bf16 "
        "{%0,%1,%2,%3,%4,%5,%6,%7,%8,%9,%10,%11,%12,%13,%14,%15,%16,%17,%18,%19,"
        "%20,%21,%22,%23,%24,%25,%26,%27,%28,%29,%30,%31,%32,%33,%34,%35,%36,%37,%38,%39,"
        "%40,%41,%42,%43,%44,%45,%46,%47,%48,%49,%50,%51,%52,%53,%54,%55,%56,%57,%58,%59,"
        "%60,%61,%62,%63,%64,%65,%66,%67,%68,%69,%70,%71,%72,%73,%74,%75,%76,%77,%78,%79,"
        "%80,%81,%82,%83,%84,%85,%86,%87,%88,%89,%90,%91,%92,%93,%94,%95}, "
        "%96, %97, p, 1, 1, 0, 1;\n}\n"
        : "+f"(d[0]), "+f"(d[1]), "+f"(d[2]), "+f"(d[3]), "+f"(d[4]), "+f"(d[5]), "+f"(d[6]), "+f"(d[7]), "+f"(d[8]), "+f"(d[9]),
          "+f"(d[10]), "+f"(d[11]), "+f"(d[12]), "+f"(d[13]), "+f"(d[14]), "+f"(d[15]), "+f"(d[16]), "+f"(d[17]), "+f"(d[18]), "+f"(d[19]),
          "+f"(d[20]), "+f"(d[21]), "+f"(d[22]), "+f"(d[23]), "+f"(d[24]), "+f"(d[25]), "+f"(d[26]), "+f"(d[27]), "+f"(d[28]), "+f"(d[29]),
          "+f"(d[30]), "+f"(d[31]), "+f"(d[32]), "+f"(d[33]), "+f"(d[34]), "+f"(d[35]), "+f"(d[36]), "+f"(d[37]), "+f"(d[38]), "+f"(d[39]),
          "+f"(d[40]), "+f"(d[41]), "+f"(d[42]), "+f"(d[43]), "+f"(d[44]), "+f"(d[45]), "+f"(d[46]), "+f"(d[47]), "+f"(d[48]), "+f"(d[49]),
          "+f"(d[50]), "+f"(d[51]), "+f"(d[52]), "+f"(d[53]), "+f"(d[54]), "+f"(d[55]), "+f"(d[56]), "+f"(d[57]), "+f"(d[58]), "+f"(d[59]),
          "+f"(d[60]), "+f"(d[61]), "+f"(d[62]), "+f"(d[63]), "+f"(d[64]), "+f"(d[65]), "+f"(d[66]), "+f"(d[67]), "+f"(d[68]), "+f"(d[69]),
          "+f"(d[70]), "+f"(d[71]), "+f"(d[72]), "+f"(d[73]), "+f"(d[74]), "+f"(d[75]), "+f"(d[76]), "+f"(d[77]), "+f"(d[78]), "+f"(d[79]),
          "+f"(d[80]), "+f"(d[81]), "+f"(d[82]), "+f"(d[83]), "+f"(d[84]), "+f"(d[85]), "+f"(d[86]), "+f"(d[87]), "+f"(d[88]), "+f"(d[89]),
          "+f"(d[90]), "+f"(d[91]), "+f"(d[92]), "+f"(d[93]), "+f"(d[94]), "+f"(d[95])
        : "l"(da), "l"(db));
}
__device__ __forceinline__ void wgmma_ss(float (&d)[64], uint64_t da, uint64_t db) {
    asm volatile("{\n.reg .pred p;\nsetp.eq.b32 p, 0, 0;\n"
        "wgmma.mma_async.sync.aligned.m64n128k16.f32.bf16.bf16 "
        "{%0,%1,%2,%3,%4,%5,%6,%7,%8,%9,%10,%11,%12,%13,%14,%15,%16,%17,%18,%19,"
        "%20,%21,%22,%23,%24,%25,%26,%27,%28,%29,%30,%31,%32,%33,%34,%35,%36,%37,%38,%39,"
        "%40,%41,%42,%43,%44,%45,%46,%47,%48,%49,%50,%51,%52,%53,%54,%55,%56,%57,%58,%59,"
        "%60,%61,%62,%63}, "
        "%64, %65, p, 1, 1, 0, 1;\n}\n"
        : "+f"(d[0]), "+f"(d[1]), "+f"(d[2]), "+f"(d[3]), "+f"(d[4]), "+f"(d[5]), "+f"(d[6]), "+f"(d[7]), "+f"(d[8]), "+f"(d[9]),
          "+f"(d[10]), "+f"(d[11]), "+f"(d[12]), "+f"(d[13]), "+f"(d[14]), "+f"(d[15]), "+f"(d[16]), "+f"(d[17]), "+f"(d[18]), "+f"(d[19]),
          "+f"(d[20]), "+f"(d[21]), "+f"(d[22]), "+f"(d[23]), "+f"(d[24]), "+f"(d[25]), "+f"(d[26]), "+f"(d[27]), "+f"(d[28]), "+f"(d[29]),
          "+f"(d[30]), "+f"(d[31]), "+f"(d[32]), "+f"(d[33]), "+f"(d[34]), "+f"(d[35]), "+f"(d[36]), "+f"(d[37]), "+f"(d[38]), "+f"(d[39]),
          "+f"(d[40]), "+f"(d[41]), "+f"(d[42]), "+f"(d[43]), "+f"(d[44]), "+f"(d[45]), "+f"(d[46]), "+f"(d[47]), "+f"(d[48]), "+f"(d[49]),
          "+f"(d[50]), "+f"(d[51]), "+f"(d[52]), "+f"(d[53]), "+f"(d[54]), "+f"(d[55]), "+f"(d[56]), "+f"(d[57]), "+f"(d[58]), "+f"(d[59]),
          "+f"(d[60]), "+f"(d[61]), "+f"(d[62]), "+f"(d[63])
        : "l"(da), "l"(db));
}
__device__ __forceinline__ void wgmma_ss(float (&d)[56], uint64_t da, uint64_t db) {
    asm volatile("{\n.reg .pred p;\nsetp.eq.b32 p, 0, 0;\n"
        "wgmma.mma_async.sync.aligned.m64n112k16.f32.bf16.bf16 "
        "{%0,%1,%2,%3,%4,%5,%6,%7,%8,%9,%10,%11,%12,%13,%14,%15,%16,%17,%18,%19,"
        "%20,%21,%22,%23,%24,%25,%26,%27,%28,%29,%30,%31,%32,%33,%34,%35,%36,%37,%38,%39,"
        "%40,%41,%42,%43,%44,%45,%46,%47,%48,%49,%50,%51,%52,%53,%54,%55}, "
        "%56, %57, p, 1, 1, 0, 1;\n}\n"
        : "+f"(d[0]), "+f"(d[1]), "+f"(d[2]), "+f"(d[3]), "+f"(d[4]), "+f"(d[5]), "+f"(d[6]), "+f"(d[7]), "+f"(d[8]), "+f"(d[9]),
          "+f"(d[10]), "+f"(d[11]), "+f"(d[12]), "+f"(d[13]), "+f"(d[14]), "+f"(d[15]), "+f"(d[16]), "+f"(d[17]), "+f"(d[18]), "+f"(d[19]),
          "+f"(d[20]), "+f"(d[21]), "+f"(d[22]), "+f"(d[23]), "+f"(d[24]), "+f"(d[25]), "+f"(d[26]), "+f"(d[27]), "+f"(d[28]), "+f"(d[29]),
          "+f"(d[30]), "+f"(d[31]), "+f"(d[32]), "+f"(d[33]), "+f"(d[34]), "+f"(d[35]), "+f"(d[36]), "+f"(d[37]), "+f"(d[38]), "+f"(d[39]),
          "+f"(d[40]), "+f"(d[41]), "+f"(d[42]), "+f"(d[43]), "+f"(d[44]), "+f"(d[45]), "+f"(d[46]), "+f"(d[47]), "+f"(d[48]), "+f"(d[49]),
          "+f"(d[50]), "+f"(d[51]), "+f"(d[52]), "+f"(d[53]), "+f"(d[54]), "+f"(d[55])
        : "l"(da), "l"(db));
}
__device__ __forceinline__ void wgmma_ss(float (&d)[24], uint64_t da, uint64_t db) {
    asm volatile("{\n.reg .pred p;\nsetp.eq.b32 p, 0, 0;\n"
        "wgmma.mma_async.sync.aligned.m64n48k16.f32.bf16.bf16 "
        "{%0,%1,%2,%3,%4,%5,%6,%7,%8,%9,%10,%11,%12,%13,%14,%15,%16,%17,%18,%19,"
        "%20,%21,%22,%23}, "
        "%24, %25, p, 1, 1, 0, 1;\n}\n"
        : "+f"(d[0]), "+f"(d[1]), "+f"(d[2]), "+f"(d[3]), "+f"(d[4]), "+f"(d[5]), "+f"(d[6]), "+f"(d[7]), "+f"(d[8]), "+f"(d[9]),
          "+f"(d[10]), "+f"(d[11]), "+f"(d[12]), "+f"(d[13]), "+f"(d[14]), "+f"(d[15]), "+f"(d[16]), "+f"(d[17]), "+f"(d[18]), "+f"(d[19]),
          "+f"(d[20]), "+f"(d[21]), "+f"(d[22]), "+f"(d[23])
        : "l"(da), "l"(db));
}
__device__ __forceinline__ void wgmma_ssf(float (&d)[96], uint64_t da, uint64_t db) {
    asm volatile("{\n.reg .pred p;\nsetp.ne.b32 p, 0, 0;\n"
        "wgmma.mma_async.sync.aligned.m64n192k16.f32.bf16.bf16 "
        "{%0,%1,%2,%3,%4,%5,%6,%7,%8,%9,%10,%11,%12,%13,%14,%15,%16,%17,%18,%19,"
        "%20,%21,%22,%23,%24,%25,%26,%27,%28,%29,%30,%31,%32,%33,%34,%35,%36,%37,%38,%39,"
        "%40,%41,%42,%43,%44,%45,%46,%47,%48,%49,%50,%51,%52,%53,%54,%55,%56,%57,%58,%59,"
        "%60,%61,%62,%63,%64,%65,%66,%67,%68,%69,%70,%71,%72,%73,%74,%75,%76,%77,%78,%79,"
        "%80,%81,%82,%83,%84,%85,%86,%87,%88,%89,%90,%91,%92,%93,%94,%95}, "
        "%96, %97, p, 1, 1, 0, 1;\n}\n"
        : "=f"(d[0]), "=f"(d[1]), "=f"(d[2]), "=f"(d[3]), "=f"(d[4]), "=f"(d[5]), "=f"(d[6]), "=f"(d[7]), "=f"(d[8]), "=f"(d[9]),
          "=f"(d[10]), "=f"(d[11]), "=f"(d[12]), "=f"(d[13]), "=f"(d[14]), "=f"(d[15]), "=f"(d[16]), "=f"(d[17]), "=f"(d[18]), "=f"(d[19]),
          "=f"(d[20]), "=f"(d[21]), "=f"(d[22]), "=f"(d[23]), "=f"(d[24]), "=f"(d[25]), "=f"(d[26]), "=f"(d[27]), "=f"(d[28]), "=f"(d[29]),
          "=f"(d[30]), "=f"(d[31]), "=f"(d[32]), "=f"(d[33]), "=f"(d[34]), "=f"(d[35]), "=f"(d[36]), "=f"(d[37]), "=f"(d[38]), "=f"(d[39]),
          "=f"(d[40]), "=f"(d[41]), "=f"(d[42]), "=f"(d[43]), "=f"(d[44]), "=f"(d[45]), "=f"(d[46]), "=f"(d[47]), "=f"(d[48]), "=f"(d[49]),
          "=f"(d[50]), "=f"(d[51]), "=f"(d[52]), "=f"(d[53]), "=f"(d[54]), "=f"(d[55]), "=f"(d[56]), "=f"(d[57]), "=f"(d[58]), "=f"(d[59]),
          "=f"(d[60]), "=f"(d[61]), "=f"(d[62]), "=f"(d[63]), "=f"(d[64]), "=f"(d[65]), "=f"(d[66]), "=f"(d[67]), "=f"(d[68]), "=f"(d[69]),
          "=f"(d[70]), "=f"(d[71]), "=f"(d[72]), "=f"(d[73]), "=f"(d[74]), "=f"(d[75]), "=f"(d[76]), "=f"(d[77]), "=f"(d[78]), "=f"(d[79]),
          "=f"(d[80]), "=f"(d[81]), "=f"(d[82]), "=f"(d[83]), "=f"(d[84]), "=f"(d[85]), "=f"(d[86]), "=f"(d[87]), "=f"(d[88]), "=f"(d[89]),
          "=f"(d[90]), "=f"(d[91]), "=f"(d[92]), "=f"(d[93]), "=f"(d[94]), "=f"(d[95])
        : "l"(da), "l"(db));
}
__device__ __forceinline__ void wgmma_ssf(float (&d)[64], uint64_t da, uint64_t db) {
    asm volatile("{\n.reg .pred p;\nsetp.ne.b32 p, 0, 0;\n"
        "wgmma.mma_async.sync.aligned.m64n128k16.f32.bf16.bf16 "
        "{%0,%1,%2,%3,%4,%5,%6,%7,%8,%9,%10,%11,%12,%13,%14,%15,%16,%17,%18,%19,"
        "%20,%21,%22,%23,%24,%25,%26,%27,%28,%29,%30,%31,%32,%33,%34,%35,%36,%37,%38,%39,"
        "%40,%41,%42,%43,%44,%45,%46,%47,%48,%49,%50,%51,%52,%53,%54,%55,%56,%57,%58,%59,"
        "%60,%61,%62,%63}, "
        "%64, %65, p, 1, 1, 0, 1;\n}\n"
        : "=f"(d[0]), "=f"(d[1]), "=f"(d[2]), "=f"(d[3]), "=f"(d[4]), "=f"(d[5]), "=f"(d[6]), "=f"(d[7]), "=f"(d[8]), "=f"(d[9]),
          "=f"(d[10]), "=f"(d[11]), "=f"(d[12]), "=f"(d[13]), "=f"(d[14]), "=f"(d[15]), "=f"(d[16]), "=f"(d[17]), "=f"(d[18]), "=f"(d[19]),
          "=f"(d[20]), "=f"(d[21]), "=f"(d[22]), "=f"(d[23]), "=f"(d[24]), "=f"(d[25]), "=f"(d[26]), "=f"(d[27]), "=f"(d[28]), "=f"(d[29]),
          "=f"(d[30]), "=f"(d[31]), "=f"(d[32]), "=f"(d[33]), "=f"(d[34]), "=f"(d[35]), "=f"(d[36]), "=f"(d[37]), "=f"(d[38]), "=f"(d[39]),
          "=f"(d[40]), "=f"(d[41]), "=f"(d[42]), "=f"(d[43]), "=f"(d[44]), "=f"(d[45]), "=f"(d[46]), "=f"(d[47]), "=f"(d[48]), "=f"(d[49]),
          "=f"(d[50]), "=f"(d[51]), "=f"(d[52]), "=f"(d[53]), "=f"(d[54]), "=f"(d[55]), "=f"(d[56]), "=f"(d[57]), "=f"(d[58]), "=f"(d[59]),
          "=f"(d[60]), "=f"(d[61]), "=f"(d[62]), "=f"(d[63])
        : "l"(da), "l"(db));
}
__device__ __forceinline__ void wgmma_ssf(float (&d)[56], uint64_t da, uint64_t db) {
    asm volatile("{\n.reg .pred p;\nsetp.ne.b32 p, 0, 0;\n"
        "wgmma.mma_async.sync.aligned.m64n112k16.f32.bf16.bf16 "
        "{%0,%1,%2,%3,%4,%5,%6,%7,%8,%9,%10,%11,%12,%13,%14,%15,%16,%17,%18,%19,"
        "%20,%21,%22,%23,%24,%25,%26,%27,%28,%29,%30,%31,%32,%33,%34,%35,%36,%37,%38,%39,"
        "%40,%41,%42,%43,%44,%45,%46,%47,%48,%49,%50,%51,%52,%53,%54,%55}, "
        "%56, %57, p, 1, 1, 0, 1;\n}\n"
        : "=f"(d[0]), "=f"(d[1]), "=f"(d[2]), "=f"(d[3]), "=f"(d[4]), "=f"(d[5]), "=f"(d[6]), "=f"(d[7]), "=f"(d[8]), "=f"(d[9]),
          "=f"(d[10]), "=f"(d[11]), "=f"(d[12]), "=f"(d[13]), "=f"(d[14]), "=f"(d[15]), "=f"(d[16]), "=f"(d[17]), "=f"(d[18]), "=f"(d[19]),
          "=f"(d[20]), "=f"(d[21]), "=f"(d[22]), "=f"(d[23]), "=f"(d[24]), "=f"(d[25]), "=f"(d[26]), "=f"(d[27]), "=f"(d[28]), "=f"(d[29]),
          "=f"(d[30]), "=f"(d[31]), "=f"(d[32]), "=f"(d[33]), "=f"(d[34]), "=f"(d[35]), "=f"(d[36]), "=f"(d[37]), "=f"(d[38]), "=f"(d[39]),
          "=f"(d[40]), "=f"(d[41]), "=f"(d[42]), "=f"(d[43]), "=f"(d[44]), "=f"(d[45]), "=f"(d[46]), "=f"(d[47]), "=f"(d[48]), "=f"(d[49]),
          "=f"(d[50]), "=f"(d[51]), "=f"(d[52]), "=f"(d[53]), "=f"(d[54]), "=f"(d[55])
        : "l"(da), "l"(db));
}
__device__ __forceinline__ void wgmma_ssf(float (&d)[24], uint64_t da, uint64_t db) {
    asm volatile("{\n.reg .pred p;\nsetp.ne.b32 p, 0, 0;\n"
        "wgmma.mma_async.sync.aligned.m64n48k16.f32.bf16.bf16 "
        "{%0,%1,%2,%3,%4,%5,%6,%7,%8,%9,%10,%11,%12,%13,%14,%15,%16,%17,%18,%19,"
        "%20,%21,%22,%23}, "
        "%24, %25, p, 1, 1, 0, 1;\n}\n"
        : "=f"(d[0]), "=f"(d[1]), "=f"(d[2]), "=f"(d[3]), "=f"(d[4]), "=f"(d[5]), "=f"(d[6]), "=f"(d[7]), "=f"(d[8]), "=f"(d[9]),
          "=f"(d[10]), "=f"(d[11]), "=f"(d[12]), "=f"(d[13]), "=f"(d[14]), "=f"(d[15]), "=f"(d[16]), "=f"(d[17]), "=f"(d[18]), "=f"(d[19]),
          "=f"(d[20]), "=f"(d[21]), "=f"(d[22]), "=f"(d[23])
        : "l"(da), "l"(db));
}
__device__ __forceinline__ void wgmma_rs80(float (&d)[40], uint32_t a0, uint32_t a1, uint32_t a2, uint32_t a3, uint64_t db) {
    asm volatile("{\n.reg .pred p;\nsetp.eq.b32 p, 0, 0;\n"
        "wgmma.mma_async.sync.aligned.m64n80k16.f32.bf16.bf16 "
        "{%0,%1,%2,%3,%4,%5,%6,%7,%8,%9,%10,%11,%12,%13,%14,%15,%16,%17,%18,%19,"
        "%20,%21,%22,%23,%24,%25,%26,%27,%28,%29,%30,%31,%32,%33,%34,%35,%36,%37,%38,%39}, "
        "{%40,%41,%42,%43}, %44, p, 1, 1, 1;\n}\n"
        : "+f"(d[0]), "+f"(d[1]), "+f"(d[2]), "+f"(d[3]), "+f"(d[4]), "+f"(d[5]), "+f"(d[6]), "+f"(d[7]), "+f"(d[8]), "+f"(d[9]),
          "+f"(d[10]), "+f"(d[11]), "+f"(d[12]), "+f"(d[13]), "+f"(d[14]), "+f"(d[15]), "+f"(d[16]), "+f"(d[17]), "+f"(d[18]), "+f"(d[19]),
          "+f"(d[20]), "+f"(d[21]), "+f"(d[22]), "+f"(d[23]), "+f"(d[24]), "+f"(d[25]), "+f"(d[26]), "+f"(d[27]), "+f"(d[28]), "+f"(d[29]),
          "+f"(d[30]), "+f"(d[31]), "+f"(d[32]), "+f"(d[33]), "+f"(d[34]), "+f"(d[35]), "+f"(d[36]), "+f"(d[37]), "+f"(d[38]), "+f"(d[39])
        : "r"(a0), "r"(a1), "r"(a2), "r"(a3), "l"(db));
}
__device__ __forceinline__ void wgmma_rs80f(float (&d)[40], uint32_t a0, uint32_t a1, uint32_t a2, uint32_t a3, uint64_t db) {
    asm volatile("{\n.reg .pred p;\nsetp.ne.b32 p, 0, 0;\n"
        "wgmma.mma_async.sync.aligned.m64n80k16.f32.bf16.bf16 "
        "{%0,%1,%2,%3,%4,%5,%6,%7,%8,%9,%10,%11,%12,%13,%14,%15,%16,%17,%18,%19,"
        "%20,%21,%22,%23,%24,%25,%26,%27,%28,%29,%30,%31,%32,%33,%34,%35,%36,%37,%38,%39}, "
        "{%40,%41,%42,%43}, %44, p, 1, 1, 1;\n}\n"
        : "=f"(d[0]), "=f"(d[1]), "=f"(d[2]), "=f"(d[3]), "=f"(d[4]), "=f"(d[5]), "=f"(d[6]), "=f"(d[7]), "=f"(d[8]), "=f"(d[9]),
          "=f"(d[10]), "=f"(d[11]), "=f"(d[12]), "=f"(d[13]), "=f"(d[14]), "=f"(d[15]), "=f"(d[16]), "=f"(d[17]), "=f"(d[18]), "=f"(d[19]),
          "=f"(d[20]), "=f"(d[21]), "=f"(d[22]), "=f"(d[23]), "=f"(d[24]), "=f"(d[25]), "=f"(d[26]), "=f"(d[27]), "=f"(d[28]), "=f"(d[29]),
          "=f"(d[30]), "=f"(d[31]), "=f"(d[32]), "=f"(d[33]), "=f"(d[34]), "=f"(d[35]), "=f"(d[36]), "=f"(d[37]), "=f"(d[38]), "=f"(d[39])
        : "r"(a0), "r"(a1), "r"(a2), "r"(a3), "l"(db));
}
__device__ __forceinline__ void wgmma_qk0(float (&d)[32], uint32_t a0, uint32_t a1, uint32_t a2, uint32_t a3, uint64_t db) {
    asm volatile("{\n.reg .pred p;\nsetp.ne.b32 p, 0, 0;\n"
        "wgmma.mma_async.sync.aligned.m64n64k16.f32.bf16.bf16 "
        "{%0,%1,%2,%3,%4,%5,%6,%7,%8,%9,%10,%11,%12,%13,%14,%15,%16,%17,%18,%19,"
        "%20,%21,%22,%23,%24,%25,%26,%27,%28,%29,%30,%31}, "
        "{%32,%33,%34,%35}, %36, p, 1, 1, 0;\n}\n"
        : "=f"(d[0]), "=f"(d[1]), "=f"(d[2]), "=f"(d[3]), "=f"(d[4]), "=f"(d[5]), "=f"(d[6]), "=f"(d[7]), "=f"(d[8]), "=f"(d[9]),
          "=f"(d[10]), "=f"(d[11]), "=f"(d[12]), "=f"(d[13]), "=f"(d[14]), "=f"(d[15]), "=f"(d[16]), "=f"(d[17]), "=f"(d[18]), "=f"(d[19]),
          "=f"(d[20]), "=f"(d[21]), "=f"(d[22]), "=f"(d[23]), "=f"(d[24]), "=f"(d[25]), "=f"(d[26]), "=f"(d[27]), "=f"(d[28]), "=f"(d[29]),
          "=f"(d[30]), "=f"(d[31])
        : "r"(a0), "r"(a1), "r"(a2), "r"(a3), "l"(db));
}
__device__ __forceinline__ void wgmma_qk1(float (&d)[32], uint32_t a0, uint32_t a1, uint32_t a2, uint32_t a3, uint64_t db) {
    asm volatile("{\n.reg .pred p;\nsetp.eq.b32 p, 0, 0;\n"
        "wgmma.mma_async.sync.aligned.m64n64k16.f32.bf16.bf16 "
        "{%0,%1,%2,%3,%4,%5,%6,%7,%8,%9,%10,%11,%12,%13,%14,%15,%16,%17,%18,%19,"
        "%20,%21,%22,%23,%24,%25,%26,%27,%28,%29,%30,%31}, "
        "{%32,%33,%34,%35}, %36, p, 1, 1, 0;\n}\n"
        : "+f"(d[0]), "+f"(d[1]), "+f"(d[2]), "+f"(d[3]), "+f"(d[4]), "+f"(d[5]), "+f"(d[6]), "+f"(d[7]), "+f"(d[8]), "+f"(d[9]),
          "+f"(d[10]), "+f"(d[11]), "+f"(d[12]), "+f"(d[13]), "+f"(d[14]), "+f"(d[15]), "+f"(d[16]), "+f"(d[17]), "+f"(d[18]), "+f"(d[19]),
          "+f"(d[20]), "+f"(d[21]), "+f"(d[22]), "+f"(d[23]), "+f"(d[24]), "+f"(d[25]), "+f"(d[26]), "+f"(d[27]), "+f"(d[28]), "+f"(d[29]),
          "+f"(d[30]), "+f"(d[31])
        : "r"(a0), "r"(a1), "r"(a2), "r"(a3), "l"(db));
}
__device__ __forceinline__ void wgmma_pv(float (&d)[12], uint32_t a0, uint32_t a1, uint32_t a2, uint32_t a3, uint64_t db) {
    asm volatile("{\n.reg .pred p;\nsetp.eq.b32 p, 0, 0;\n"
        "wgmma.mma_async.sync.aligned.m64n24k16.f32.bf16.bf16 "
        "{%0,%1,%2,%3,%4,%5,%6,%7,%8,%9,%10,%11}, "
        "{%12,%13,%14,%15}, %16, p, 1, 1, 1;\n}\n"
        : "+f"(d[0]), "+f"(d[1]), "+f"(d[2]), "+f"(d[3]), "+f"(d[4]), "+f"(d[5]), "+f"(d[6]), "+f"(d[7]), "+f"(d[8]), "+f"(d[9]),
          "+f"(d[10]), "+f"(d[11])
        : "r"(a0), "r"(a1), "r"(a2), "r"(a3), "l"(db));
}
__device__ __forceinline__ void wgmma_pvn(float (&d)[12], uint32_t a0, uint32_t a1, uint32_t a2, uint32_t a3, uint64_t db) {
    asm volatile("{\n.reg .pred p;\nsetp.eq.b32 p, 0, 0;\n"
        "wgmma.mma_async.sync.aligned.m64n24k16.f32.bf16.bf16 "
        "{%0,%1,%2,%3,%4,%5,%6,%7,%8,%9,%10,%11}, "
        "{%12,%13,%14,%15}, %16, p, -1, 1, 1;\n}\n"
        : "+f"(d[0]), "+f"(d[1]), "+f"(d[2]), "+f"(d[3]), "+f"(d[4]), "+f"(d[5]), "+f"(d[6]), "+f"(d[7]), "+f"(d[8]), "+f"(d[9]),
          "+f"(d[10]), "+f"(d[11])
        : "r"(a0), "r"(a1), "r"(a2), "r"(a3), "l"(db));
}
__device__ __forceinline__ void wgmma_pv0(float (&d)[12], uint32_t a0, uint32_t a1, uint32_t a2, uint32_t a3, uint64_t db) {
    asm volatile("{\n.reg .pred p;\nsetp.ne.b32 p, 0, 0;\n"
        "wgmma.mma_async.sync.aligned.m64n24k16.f32.bf16.bf16 "
        "{%0,%1,%2,%3,%4,%5,%6,%7,%8,%9,%10,%11}, "
        "{%12,%13,%14,%15}, %16, p, 1, 1, 1;\n}\n"
        : "=f"(d[0]), "=f"(d[1]), "=f"(d[2]), "=f"(d[3]), "=f"(d[4]), "=f"(d[5]), "=f"(d[6]), "=f"(d[7]), "=f"(d[8]), "=f"(d[9]),
          "=f"(d[10]), "=f"(d[11])
        : "r"(a0), "r"(a1), "r"(a2), "r"(a3), "l"(db));
}
__device__ __forceinline__ void wgmma_l64a(float (&d)[32], uint64_t da, uint64_t db) {
    asm volatile("{\n.reg .pred p;\nsetp.ne.b32 p, 0, 0;\n"
        "wgmma.mma_async.sync.aligned.m64n64k16.f32.bf16.bf16 "
        "{%0,%1,%2,%3,%4,%5,%6,%7,%8,%9,%10,%11,%12,%13,%14,%15,%16,%17,%18,%19,"
        "%20,%21,%22,%23,%24,%25,%26,%27,%28,%29,%30,%31}, "
        "%32, %33, p, 1, 1, 0, 0;\n}\n"
        : "=f"(d[0]), "=f"(d[1]), "=f"(d[2]), "=f"(d[3]), "=f"(d[4]), "=f"(d[5]), "=f"(d[6]), "=f"(d[7]), "=f"(d[8]), "=f"(d[9]),
          "=f"(d[10]), "=f"(d[11]), "=f"(d[12]), "=f"(d[13]), "=f"(d[14]), "=f"(d[15]), "=f"(d[16]), "=f"(d[17]), "=f"(d[18]), "=f"(d[19]),
          "=f"(d[20]), "=f"(d[21]), "=f"(d[22]), "=f"(d[23]), "=f"(d[24]), "=f"(d[25]), "=f"(d[26]), "=f"(d[27]), "=f"(d[28]), "=f"(d[29]),
          "=f"(d[30]), "=f"(d[31])
        : "l"(da), "l"(db));
}
__device__ __forceinline__ void wgmma_l64b(float (&d)[32], uint64_t da, uint64_t db) {
    asm volatile("{\n.reg .pred p;\nsetp.eq.b32 p, 0, 0;\n"
        "wgmma.mma_async.sync.aligned.m64n64k16.f32.bf16.bf16 "
        "{%0,%1,%2,%3,%4,%5,%6,%7,%8,%9,%10,%11,%12,%13,%14,%15,%16,%17,%18,%19,"
        "%20,%21,%22,%23,%24,%25,%26,%27,%28,%29,%30,%31}, "
        "%32, %33, p, 1, 1, 0, 0;\n}\n"
        : "+f"(d[0]), "+f"(d[1]), "+f"(d[2]), "+f"(d[3]), "+f"(d[4]), "+f"(d[5]), "+f"(d[6]), "+f"(d[7]), "+f"(d[8]), "+f"(d[9]),
          "+f"(d[10]), "+f"(d[11]), "+f"(d[12]), "+f"(d[13]), "+f"(d[14]), "+f"(d[15]), "+f"(d[16]), "+f"(d[17]), "+f"(d[18]), "+f"(d[19]),
          "+f"(d[20]), "+f"(d[21]), "+f"(d[22]), "+f"(d[23]), "+f"(d[24]), "+f"(d[25]), "+f"(d[26]), "+f"(d[27]), "+f"(d[28]), "+f"(d[29]),
          "+f"(d[30]), "+f"(d[31])
        : "l"(da), "l"(db));
}
__device__ __forceinline__ void wgmma_l16a(float (&d)[8], uint64_t da, uint64_t db) {
    asm volatile("{\n.reg .pred p;\nsetp.ne.b32 p, 0, 0;\n"
        "wgmma.mma_async.sync.aligned.m64n16k16.f32.bf16.bf16 "
        "{%0,%1,%2,%3,%4,%5,%6,%7}, "
        "%8, %9, p, 1, 1, 0, 0;\n}\n"
        : "=f"(d[0]), "=f"(d[1]), "=f"(d[2]), "=f"(d[3]), "=f"(d[4]), "=f"(d[5]), "=f"(d[6]), "=f"(d[7])
        : "l"(da), "l"(db));
}
__device__ __forceinline__ void wgmma_l16b(float (&d)[8], uint64_t da, uint64_t db) {
    asm volatile("{\n.reg .pred p;\nsetp.eq.b32 p, 0, 0;\n"
        "wgmma.mma_async.sync.aligned.m64n16k16.f32.bf16.bf16 "
        "{%0,%1,%2,%3,%4,%5,%6,%7}, "
        "%8, %9, p, 1, 1, 0, 0;\n}\n"
        : "+f"(d[0]), "+f"(d[1]), "+f"(d[2]), "+f"(d[3]), "+f"(d[4]), "+f"(d[5]), "+f"(d[6]), "+f"(d[7])
        : "l"(da), "l"(db));
}

__device__ __forceinline__ uint32_t exp2_pair_fma(float a, float b) {
    const uint32_t y = __byte_perm(__float_as_uint(a), __float_as_uint(b), 0x6521);
    const uint32_t z = 0xFE7BFE7Bu - y;
    const uint32_t e = hfma2(y, z, 0x3F053F05u);
    return hfma2(y, e, y);
}
__device__ __forceinline__ void qk_tile(float (&s)[32], const uint32_t (&q)[8], uint64_t dk0, uint64_t dk1) {
    wgmma_qk0(s, q[0], q[1], q[2], q[3], dk0);
    wgmma_qk1(s, q[4], q[5], q[6], q[7], dk1);
}
#define TV 18
__device__ __forceinline__ void exp_pv_tile(const float (&s)[32], uint32_t (&p)[16], float (&o)[12], uint64_t dv, const int mask) {
    auto ex = [&](int j) {
        if ((mask >> (j >> 1)) & 1) { p[2 * j] = exp2_pair_fma(s[4 * j], s[4 * j + 1]); p[2 * j + 1] = exp2_pair_fma(s[4 * j + 2], s[4 * j + 3]); }
        else { p[2 * j] = pack2(ex2(s[4 * j]), ex2(s[4 * j + 1])); p[2 * j + 1] = pack2(ex2(s[4 * j + 2]), ex2(s[4 * j + 3])); }
    };
    auto pv = [&](int k) {
        if ((mask >> k) & 1) wgmma_pvn(o, p[4 * k], p[4 * k + 1], p[4 * k + 2], p[4 * k + 3], dv + k * 48);
        else wgmma_pv(o, p[4 * k], p[4 * k + 1], p[4 * k + 2], p[4 * k + 3], dv + k * 48);
    };
    auto hold = [&](int j) { asm volatile("" : "+r"(p[2 * j]), "+r"(p[2 * j + 1])::"memory"); };
    if (TV == 5) { ex(0); ex(1); ex(2); ex(3); ex(4); ex(5); ex(6); ex(7); pin(p); wg_fence(); pv(0); pv(1); pv(2); pv(3); }
    if (TV == 11) { ex(0); ex(1); ex(2); ex(3); wg_fence(); pv(0); pv(1); ex(4); ex(5); ex(6); ex(7); wg_fence(); pv(2); pv(3); }
    if (TV == 16) { ex(6); ex(0); ex(1); ex(2); hold(6); hold(2); wg_fence(); pv(0); ex(7); ex(3); ex(4); ex(5); wg_fence(); pv(1); pv(2); pv(3); }
    if (TV == 17) { ex(0); ex(1); wg_fence(); pv(0); ex(2); ex(3); ex(4); ex(5); ex(6); ex(7); wg_fence(); pv(1); pv(2); pv(3); }
    if (TV == 18) { ex(2); ex(0); ex(1); hold(2); wg_fence(); pv(0); ex(3); ex(4); ex(5); ex(6); ex(7); wg_fence(); pv(1); pv(2); pv(3); }
    if (TV == 19) { ex(0); ex(1); wg_fence(); pv(0); ex(2); ex(3); ex(4); ex(5); wg_fence(); pv(2); pv(1); ex(6); ex(7); wg_fence(); pv(3); }
    if (TV == 20) { ex(0); ex(1); wg_fence(); pv(0); ex(2); ex(4); ex(5); hold(2); wg_fence(); pv(2); ex(3); ex(6); ex(7); wg_fence(); pv(3); pv(1); }
    if (TV == 21) { ex(0); ex(1); wg_fence(); pv(0); ex(2); ex(3); ex(4); ex(5); ex(6); ex(7); wg_fence(); pv(2); pv(3); pv(1); }
    wg_commit();
}
__device__ __forceinline__ void finish_o(const float (&o)[12], uint32_t (&w)[6], int odd, float g0, float g1, int lane, float& l0, float& l1) {
    const int src = (lane & ~3) | (odd ? 0 : 2);
    l0 = __shfl_sync(0xffffffffu, o[8], src);
    l1 = __shfl_sync(0xffffffffu, o[10], src);
    float r0, r1;
    asm("rcp.approx.ftz.f32 %0, %1;" : "=f"(r0) : "f"(l0));
    asm("rcp.approx.ftz.f32 %0, %1;" : "=f"(r1) : "f"(l1));
    const float f0 = g0 * r0, f1 = g1 * r1;
#pragma unroll
    for (int d = 0; d < 3; d++) { w[2 * d] = pack2(o[4 * d] * f0, o[4 * d + 1] * f0); w[2 * d + 1] = pack2(o[4 * d + 2] * f1, o[4 * d + 3] * f1); }
}
struct OutPtr { uint8_t *p01, *p2; bool has2; };
__device__ __forceinline__ OutPtr out_ptr(uint32_t row16, uint32_t h, uint32_t gbase, uint32_t lane) {
    uint8_t* base = reinterpret_cast<uint8_t*>(g_att) + ((row16 >> 2) * 163840u + gbase * 1024u + h * 2560u + (row16 & 3) * 128u);
    const uint32_t pos = (lane >> 2) * 16 + (lane & 1) * 8, odd = h & 1, hi = (lane >> 1) & 1;
    return {base + (pos + (hi + odd) * 512), base + (pos + (odd ? 0 : 2048)), hi == odd};
}
__device__ __forceinline__ void store_o(const uint32_t (&w)[6], const OutPtr& o, int off) {
    stg64(o.p01 + off, w[0], w[1]);
    stg64(o.p01 + off + 1024, w[2], w[3]);
    if (o.has2) stg64(o.p2 + off, w[4], w[5]);
}

#define PACE 280u
#define PROMO CU_TENSOR_MAP_L2_PROMOTION_L2_256B
#define MAP 1
#define P1_NT(b) ((b) >> 4)
#define P1_MP(b) (((b) >> 1) & 7)
#define LJ 16
#define FENCE2()
#define P1_NTA(nt) (((nt) + 4) & 7)
#define S3J 22
#define S3T 14
#define S1T 9
#define S4J 18
#define S4T 5
#define S1J 10
#define G1 500u
#define G2 1200u
#define PF 2
#define SAJ 4
constexpr uint32_t SB0 = 1024;
#define STAG 8
#define STAGE 0
#define FD1 1
#define FD2 2
#define WD 2
constexpr int SLOT = 24576;
constexpr int OFF_X = 98304, OFF_R = 6 * SLOT, OFF_L = OFF_R - 1536, OFF_BAR = 9 * SLOT;
constexpr int OFF_F = OFF_BAR + 1024, OFF_G = OFF_F + 8192, SMEM_BYTES = OFF_G + 2048;
enum { B_FULL = 0, B_EMPTY = 48, B_STGB = 96, B_STGA = 104, B_RET = 112, B_NRM = 144, B_KV = 160, B_L = 200, B_WO = 208, B_XCH = 248, B_AF = 264, B_PUB = 312, B_LD = 344, B_R26 = 352, B_AE = 360, B_STG1 = 368, B_W0 = 376, B_ZERO = 400, B_MISC = 416 };
__host__ __device__ constexpr int k_off(int j) {
    return j < 8 ? (7 + (j >> 2)) * SLOT + (j & 3) * 3072 : j == 8 ? OFF_R - 6144 : j < 20 ? 3 * SLOT + (j - 9) * 3072 : j < 26 ? 36864 + (j - 20) * 3072 : (j - 26) * 3072;
}
__host__ __device__ constexpr int v_off(int j) { return k_off(j) + (j < 8 ? 4 : j == 8 ? 1 : j < 20 ? 11 : 6) * 3072; }
__host__ __device__ constexpr int wo_off(int i) { return 3 * SLOT + (i < 7 ? i : i - 7) * 20480; }
__host__ __device__ constexpr int wo_bar(int i) { return i < 3 ? 0 : i < 7 ? 1 : i - 5; }
constexpr float SCORE_LIMIT2 = 118.f * 118.f;

__device__ __forceinline__ void load_kv(uint32_t sb, int h, int i, int j0, int n, int arm) {
    const uint32_t bar = sb + OFF_BAR + B_KV + 8 * i;
    if (arm) mbar_expect_tx(bar, arm * 6144);
    bulk_g2s(sb + k_off(j0), g_qkv + (size_t)(32 + h) * HEAD_BYTES + j0 * 3072, n * 3072, bar);
    bulk_g2s(sb + v_off(j0), g_qkv + (size_t)(64 + h) * HEAD_BYTES + j0 * 3072, n * 3072, bar);
}
__device__ __forceinline__ void load_wo(uint32_t sb, int seq, int n) {
    const uint32_t bar = sb + OFF_BAR + B_WO + 8 * wo_bar(seq);
    mbar_expect_tx(bar, n * 20480);
    bulk_g2s(sb + wo_off(seq), reinterpret_cast<const uint8_t*>(g_wo) + (blockIdx.x & 7) * 204800 + seq * 20480, n * 20480, bar);
}

__device__ __forceinline__ void local_attn(uint32_t sb, uint32_t wid, uint64_t dK0, uint64_t dK1, uint64_t dV) {
    const uint32_t tid = fresh_tid(), lane = tid & 31, g = lane >> 2, t2 = (lane & 3) * 2;
    const uint32_t wg = wid >> 2, w = wid & 3;
    const uint32_t bid = fresh_bid(), h = bid >> 2, qb = bid & 3;
    const uint32_t gp = sb + OFF_G + (wg * 128 + w * 16 + g) * 4;
    const float gt[4] = {__uint_as_float(lds32(gp)), __uint_as_float(lds32(gp + 32)), __uint_as_float(lds32(gp + 256)), __uint_as_float(lds32(gp + 288))};
    const bool cur0 = t2 <= g, cur1 = t2 < g;
    mbar_wait(sb + OFF_BAR + B_L, 0);
    const uint32_t mc = (cur0 ? 0xffffu : 0u) | (cur1 ? 0xffff0000u : 0u);
    uint32_t mk[5];
    float v0[4], v1[4];
    {
        const uint64_t dq0 = dK0 + ((OFF_L >> 4) + wg * 384), dq1 = dK1 + ((OFF_L >> 4) + wg * 384);
        float sa[2][32], sc[2][8];
        wg_fence();
#pragma unroll
        for (int b = 0; b < 2; b++) {
            wgmma_l64a(sa[b], dq0 + b * 192, dq0 + b * 192 + (24576 >> 4)); wgmma_l64b(sa[b], dq1 + b * 192, dq1 + b * 192 + (24576 >> 4));
            wgmma_l16a(sc[b], dq0 + b * 192, dq0 + b * 192 + (27648 >> 4)); wgmma_l16b(sc[b], dq1 + b * 192, dq1 + b * 192 + (27648 >> 4));
        }
        wg_commit(); wg_wait<0>(); pin(sa[0]); pin(sa[1]); pin(sc[0]); pin(sc[1]);
#define LS(B, BLK, R, E) ((BLK) < 4 ? sa[B][((BLK) * 8 + (R) * 6 + (E)) & 31] : sc[B][(R) * 6 + (E)])
#define LWIN(W) { _Pragma("unroll") for (int i = 0; i < 4; i++) { v0[i] = cur0 ? LS(i >> 1, (W) + 1, i & 1, 0) : LS(i >> 1, W, i & 1, 0); \
                                                                 v1[i] = cur1 ? LS(i >> 1, (W) + 1, i & 1, 1) : LS(i >> 1, W, i & 1, 1); } \
                  _Pragma("unroll") for (int ks = 0; ks < 5; ks++) mk[ks] = ks == (W) ? ~mc : ks == (W) + 1 ? mc : 0u; pin(mk); }
        if (w == 0) LWIN(0) else if (w == 1) LWIN(1) else if (w == 2) LWIN(2) else LWIN(3)
#undef LWIN
#undef LS
    }
    if (qb == 0 && wid == 0) {
        if (!cur0) v0[0] = v0[1] = -INFINITY;
        if (!cur1) v1[0] = v1[1] = -INFINITY;
    }
    float m[4], l[4];
#pragma unroll
    for (int i = 0; i < 4; i++) m[i] = fmaxf(v0[i], v1[i]);
#pragma unroll
    for (int i = 0; i < 4; i++) m[i] = fmaxf(m[i], __shfl_xor_sync(0xffffffffu, m[i], 1));
#pragma unroll
    for (int i = 0; i < 4; i++) m[i] = fmaxf(m[i], __shfl_xor_sync(0xffffffffu, m[i], 2));
#pragma unroll
    for (int i = 0; i < 4; i++) { v0[i] = ex2(v0[i] - m[i]); v1[i] = ex2(v1[i] - m[i]); l[i] = v0[i] + v1[i]; }
#pragma unroll
    for (int i = 0; i < 4; i++) l[i] += __shfl_xor_sync(0xffffffffu, l[i], 1);
#pragma unroll
    for (int i = 0; i < 4; i++) l[i] += __shfl_xor_sync(0xffffffffu, l[i], 2);
    uint32_t pp[4];
#pragma unroll
    for (int i = 0; i < 4; i++) {
        float r;
        asm("rcp.approx.ftz.f32 %0, %1;" : "=f"(r) : "f"(l[i]));
        r *= gt[i];
        pp[i] = pack2(v0[i] * r, v1[i] * r);
    }
    uint32_t p[2][20];
#pragma unroll
    for (int ks = 0; ks < 5; ks++) {
#pragma unroll
        for (int b = 0; b < 2; b++) { p[b][4 * ks] = pp[2 * b] & mk[ks]; p[b][4 * ks + 1] = p[b][4 * ks + 2] = 0u; p[b][4 * ks + 3] = pp[2 * b + 1] & mk[ks]; }
    }
    pin(p[0]); pin(p[1]);
    const uint64_t dv = dV + (((OFF_L + 24576 + 25344) >> 4) + wg * 384);
    float o[2][12];
    wg_fence();
#pragma unroll
    for (int b = 0; b < 2; b++) {
        wgmma_pv0(o[b], p[b][0], p[b][1], p[b][2], p[b][3], dv + b * 192);
#pragma unroll
        for (int ks = 1; ks < 5; ks++) wgmma_pv(o[b], p[b][4 * ks], p[b][4 * ks + 1], p[b][4 * ks + 2], p[b][4 * ks + 3], dv + b * 192 + ks * 48);
    }
    wg_commit();
    const OutPtr op = out_ptr(qb * 32 + wg * 8 + w, h, 0, lane);
    wg_wait<0>(); pin(o[0]); pin(o[1]);
#pragma unroll
    for (int b = 0; b < 2; b++) {
        uint32_t wv[6];
#pragma unroll
        for (int i = 0; i < 6; i++) wv[i] = pack2(o[b][2 * i], o[b][2 * i + 1]);
        store_o(wv, op, b * 163840);
    }
    __syncwarp();
    if (elect_one()) mbar_arrive(sb + OFF_BAR + B_LD);
    TR2(7, tid == 64);
}

__device__ __noinline__ void exact_rows(int h, int row16, int lane) {
    const bool aug_lane = ((lane & 3) >= 2) != ((h & 1) != 0);
    const uint8_t* a = g_qkv + (size_t)h * HEAD_BYTES + row16 * 768 + lane * 4;
    const uint8_t* gk = g_qkv + (size_t)(32 + h) * HEAD_BYTES + lane * 4;
    const uint8_t* gv = g_qkv + (size_t)(64 + h) * HEAD_BYTES + lane * 4;
    const uint32_t q0 = ldcg_u32(a), q1 = ldcg_u32(a + 384), q2 = ldcg_u32(a + 128), q3 = ldcg_u32(a + 512);
    const uint32_t q4 = aug_lane ? 0u : ldcg_u32(a + 256), q5 = aug_lane ? 0u : ldcg_u32(a + 640);
    float m0 = -INFINITY, m1 = -INFINITY;
#pragma unroll 4
    for (int kg = 0; kg < 256; kg++) {
        const uint8_t* ka = gk + kg * 384;
        float c[4] = {0.f, 0.f, 0.f, 0.f};
        mma16816(c, q0, q1, q2, q3, ldcg_u32(ka), ldcg_u32(ka + 128));
        mma1688(c, q4, q5, ldcg_u32(ka + 256));
        m0 = fmaxf(m0, fmaxf(c[0], c[1])); m1 = fmaxf(m1, fmaxf(c[2], c[3]));
    }
    m0 = fmaxf(m0, __shfl_xor_sync(0xffffffffu, m0, 1)); m1 = fmaxf(m1, __shfl_xor_sync(0xffffffffu, m1, 1));
    m0 = fmaxf(m0, __shfl_xor_sync(0xffffffffu, m0, 2)); m1 = fmaxf(m1, __shfl_xor_sync(0xffffffffu, m1, 2));
    float oc[3][4];
#pragma unroll
    for (int d = 0; d < 3; d++) oc[d][0] = oc[d][1] = oc[d][2] = oc[d][3] = 0.f;
#pragma unroll 2
    for (int kg = 0; kg < 256; kg += 2) {
        uint32_t kk[2][3], vv[2][3], pp[2][2];
#pragma unroll
        for (int e = 0; e < 2; e++)
#pragma unroll
            for (int d = 0; d < 3; d++) { kk[e][d] = ldcg_u32(gk + (kg + e) * 384 + d * 128); vv[e][d] = ldcg_u32(gv + (kg + e) * 384 + d * 128); }
#pragma unroll
        for (int e = 0; e < 2; e++) {
            float c[4] = {0.f, 0.f, 0.f, 0.f};
            mma16816(c, q0, q1, q2, q3, kk[e][0], kk[e][1]);
            mma1688(c, q4, q5, kk[e][2]);
            pp[e][0] = pack2(ex2(c[0] - m0), ex2(c[1] - m0));
            pp[e][1] = pack2(ex2(c[2] - m1), ex2(c[3] - m1));
        }
#pragma unroll
        for (int d = 0; d < 3; d++) mma16816(oc[d], pp[0][0], pp[0][1], pp[1][0], pp[1][1], movm_t(vv[0][d]), movm_t(vv[1][d]));
    }
    float o[12];
#pragma unroll
    for (int i = 0; i < 12; i++) o[i] = oc[i >> 2][i & 3];
    const int row = row16 * 16 + (lane >> 2);
    float l0, l1;
    uint32_t w[6];
    finish_o(o, w, h & 1, 1.f - ldcg_f32(g_gate + row), 1.f - ldcg_f32(g_gate + row + 8), lane, l0, l1);
    store_o(w, out_ptr(row16, h, 80, lane), 0);
}

__device__ __forceinline__ uint32_t frag2_off(int mh, int half) { return mh ? (half ? 9 * SLOT - 4096 : 36864) : OFF_F + half * 4096; }
__device__ __forceinline__ uint32_t frag_off(int mh, int item) {
    return item < 5 ? 40960 + (mh * 2 + item) * 8192 : (item == 9 && mh) ? OFF_F : mh * 40960 + (item - 5) * 8192;
}
__device__ __forceinline__ void load_frag(uint32_t sb, int bid, int mh, int part) {
    const uint32_t fb = sb + OFF_BAR + B_AF + mh * 24 + part * 8;
    const uint2* src = g_att + (((bid >> 5) * 8 + mh * 4 + ((bid >> 3) & 3)) * 160 + (bid & 1) * 40 + (part ? 64 + part * 16 : 0)) * 128;
    if (part == 0) mbar_expect_tx(fb, 24576);
    bulk_g2s(sb + frag_off(mh, part ? 3 + 2 * part : 0), src, (part == 2 && !mh) ? 24576 : 16384, fb);
    if (part == (mh ? 2 : 0)) bulk_g2s(sb + OFF_F, src + 2048, 8192, fb);
    if (part == 0 && mh) { bulk_g2s(sb + frag2_off(1, 0), src + 2048, 4096, fb); bulk_g2s(sb + frag2_off(1, 1), src + 2560, 4096, fb); }
}
__device__ __forceinline__ uint32_t* atta_out(int bid) { return g_flag + (F_ATTA + (bid & 3) * 2 + (bid >> 6)) * 32; }
__device__ __forceinline__ uint32_t* attb_out(int bid, int wg) { return g_flag + (F_ATTB + ((bid & 3) * 4 + wg) * 2 + (bid >> 6)) * 32; }
__device__ __forceinline__ uint32_t* atta_in(int bid) { return g_flag + (F_ATTA + (bid >> 5) * 2 + (bid & 1)) * 32; }
__device__ __forceinline__ uint32_t* attb_in(int bid) { return g_flag + (F_ATTB + (bid >> 3) * 2 + (bid & 1)) * 32; }
#define SVC __forceinline__
__device__ SVC void service(uint32_t sb, int step, uint32_t aflag) {
    const uint32_t bars = sb + OFF_BAR;
    const int bid = fresh_bid(), h = bid >> 2, qb = bid & 3;
    if (step == 0) {
        bulk_wait_all();
        flag_add_done(g_flag + (F_QKVA + P1_NTA(P1_NT(bid))) * 32);
        load_kv(sb, h, 3, 20, 6, 12); load_kv(sb, h, 3, 26, 6, 0);
    } else if (step == 3) {
        mbar_wait(bars + B_RET + 24, 0);
        load_wo(sb, 0, 3); load_wo(sb, 3, 4);
    } else if (step == 4) {
        mbar_wait(bars + B_LD, 0);
        flag_add_done(atta_out(bid));
    } else if (step == 2) {
        if (aflag >= 16) {
            mbar_wait(bars + B_R26, 0);
            asm volatile("fence.acquire.gpu;" ::: "memory");
            load_frag(sb, bid, 0, 0); load_frag(sb, bid, 1, 0);
        }
    } else {
        flag_wait_head(g_flag + F_QKVA * 32, h, 0);
        mbar_wait(bars + B_RET, 0);
        fence_async_smem();
        const int halo = qb ? 768 : 0;
        const uint8_t* src = g_qkv + (size_t)(96 + h) * HEAD_BYTES + qb * 24576;
        mbar_expect_tx(bars + B_L, 3 * 24576 + 2 * halo);
        bulk_g2s(sb + OFF_L, src, 24576, bars + B_L);
        bulk_g2s(sb + OFF_L + 24576 + 768 - halo, src + (size_t)32 * HEAD_BYTES - halo, 24576 + halo, bars + B_L);
        bulk_g2s(sb + OFF_L + 24576 + 25344 + 768 - halo, src + (size_t)64 * HEAD_BYTES - halo, 24576 + halo, bars + B_L);
    }
}

template <bool B> struct Bool { static constexpr bool value = B; };
struct WBox { const CUtensorMap* tm; int c0, c1; };
__device__ __forceinline__ WBox w_box(const CUtensorMap* tw, const CUtensorMap* tg, int t, int at) {
    if (t < 6) return {tw, at * 64, t};
    if (at < 3) return {tw, 256, (t - 6) * 3 + at};
    return {tg, 0, (t - 6) * 3};
}

__global__ void __cluster_dims__(2, 1, 1) __launch_bounds__(512, 1)
k_fused(const __grid_constant__ CUtensorMap tmX, const __grid_constant__ CUtensorMap tmWb, const __grid_constant__ CUtensorMap tmWa,
        const __grid_constant__ CUtensorMap tmGb, const __grid_constant__ CUtensorMap tmGa,
        const __grid_constant__ CUtensorMap tmS, const __nv_bfloat16* __restrict__ x, const __nv_bfloat16* __restrict__ gate_w,
        const uint8_t* __restrict__ wb, const uint8_t* __restrict__ woa, const uint8_t* __restrict__ wob,
        __nv_bfloat16* __restrict__ out) {
    extern __shared__ __align__(1024) uint8_t smem_raw[];
    const uint32_t sb = smem_u32(smem_raw);
    if ((sb & 0xFFFFFFu) != SB0) __trap();
    const uint32_t bars = sb + OFF_BAR;
    float* s_misc = reinterpret_cast<float*>(smem_raw + OFF_BAR + B_MISC);
    const int bid = blockIdx.x;
    const int h = bid >> 2, qb = bid & 3;

    {
        const int warp = __shfl_sync(0xffffffffu, threadIdx.x >> 5, 0), lane = threadIdx.x & 31;
        const int mt = P1_MP(bid) * 2 + (bid & 1), nt = P1_NT(bid);
        TRINIT(); TR(0, threadIdx.x == 0);
        if (warp >= 12 && warp < 12 + PF) {
            if (lane < 15) asm volatile("prefetch.global.L2 [%0];" ::"l"(wb + (warp - 12) * 245760 + bid * 1920 + lane * 128) : "memory");
            if (lane >= 16) asm volatile("prefetch.global.L2 [%0];" ::"l"(x + (size_t)(bid * 16 + lane - 16) * DM + (warp - 12) * 64) : "memory");
        }
        if (threadIdx.x == 352) {
            prefetch_tmap(&tmX);
#pragma unroll
            for (int i = 0; i < 6; i++) mbar_init(bars + B_FULL + 8 * i, 1);
            fence_mbar_init();
        } else if (threadIdx.x == 256) {
            prefetch_tmap(&tmWb); prefetch_tmap(&tmGb);
        } else if (threadIdx.x == 32) {
#pragma unroll
            for (int i = 0; i < 6; i++) mbar_init(bars + B_EMPTY + 8 * i, 16);
#pragma unroll
            for (int i = 0; i < 4; i++) mbar_init(bars + B_PUB + 8 * i, 4);
            fence_mbar_init();
        } else if (threadIdx.x == 64) {
            mbar_init(bars + B_STGB, 4); mbar_init(bars + B_STG1, 4); mbar_init(bars + B_STGA, 8);
            mbar_init(bars + B_RET, 16); mbar_init(bars + B_RET + 8, 8); mbar_init(bars + B_RET + 16, 16); mbar_init(bars + B_RET + 24, 16);
            mbar_init(bars + B_LD, 16); mbar_init(bars + B_NRM, 4);
            fence_mbar_init();
        } else if (threadIdx.x == 128) {
#pragma unroll
            for (int i = 0; i < 8; i++) mbar_init(bars + B_XCH + 8 * i, 1);
            fence_mbar_init();
#pragma unroll
            for (int i = 0; i < 2; i++) {
                mbar_expect_tx(bars + B_XCH + 8 * i, 10240);
                mbar_expect_tx(bars + B_AF + 24 * i + 8, 16384); mbar_expect_tx(bars + B_AF + 24 * i + 16, 24576);
            }
        } else if (threadIdx.x == 160) {
            mbar_init(bars + B_AE, 8); mbar_init(bars + B_R26, 16); mbar_init(bars + B_W0, 8); mbar_init(bars + B_W0 + 8, 8); mbar_init(bars + B_W0 + 16, 8);
            fence_mbar_init();
        } else if (threadIdx.x == 96) {
#pragma unroll
            for (int i = 0; i < 11; i++) mbar_init(bars + B_KV + 8 * i, i == 3 ? 2 : 1);
            s_misc[-4] = 0.f; s_misc[-3] = 0.f;
            fence_mbar_init();
        }
        __syncwarp();
        cluster_arrive();
        if (warp == 11 && elect_one()) {
            tma_x(sb + OFF_X, &tmX, 0, mt * 8, bars + B_FULL);
#pragma unroll
            for (int i = 0; i < 6; i++) mbar_expect_tx(bars + B_FULL + 8 * i, (i & 1) ? 16384 : 32768);
        }
        __syncwarp();
        cluster_wait();
        const uint32_t t_start = clock_lo();
        if ((warp == 8 || warp == 10) && elect_one()) {
            const int at = (bid & 1) * 2 + (warp == 10);
            const WBox bx = w_box(&tmWb, &tmGb, nt, at);
#pragma unroll
            for (int i = 0; i < 2; i++) tma_3d_mc(sb + i * 16384 + at * 4096, bx.tm, bx.c0, i * 32, bx.c1, bars + B_FULL + 8 * i, 3);
        }
        __syncwarp();

        if (warp < 8) {
            asm volatile("setmaxnreg.inc.sync.aligned.u32 152;");
            const int wg = warp >> 2, t = lane & 3;
            const uint64_t da0 = mkdesc(SB0 + OFF_X, 16, 1024, 1) + wg * 512, db0 = mkdesc(SB0, 4096, 1024, 1);
            uint32_t rel;
            asm volatile("mapa.shared::cluster.u32 %0, %1, %2;" : "=r"(rel) : "r"(bars + B_EMPTY), "r"(lane & 1));
            uint32_t xs = 0, xprev = 0, ph = 0;
#pragma unroll 1
            for (int br = 0; br < 2; br++) {
                const int ct = br ? P1_NTA(nt) : nt;
                auto tile = [&](auto gathered) {
                    constexpr bool G = decltype(gathered)::value;
                    constexpr int N0 = G ? 96 : 64;
                    float acc0[N0], acc1[120 - N0];
                    constexpr uint64_t dc0 = G ? mkdesc(SB0 + 12288, 1024, 256, 3) : mkdesc(SB0 + 8192, 4096, 1024, 1);
                    constexpr uint32_t dck = G ? 32 : 128;
                    bool last = false;
                    auto pair = [&](bool first) {
                        const uint64_t da = da0 + xs * 1024, db = db0 + xs * 2048, dc = dc0 + xs * 2048, dd = dc + dck;
#pragma unroll
                        for (int e = 0; e < 2; e++) {
                            mbar_wait(bars + B_FULL + 16 * xs + 8 * e, ph);
                            TR(1 + 3 * br, threadIdx.x == 0 && first && e == 0);
                            wg_fence();
                            if (first && e == 0) { wgmma_ssf(acc0, da, db); wgmma_ssf(acc1, da, dc); }
                            else { wgmma_ss(acc0, da + e * 4, db + e * 1024); wgmma_ss(acc1, da + e * 4, dc + e * 1024); }
                            wgmma_ss(acc0, da + e * 4 + 2, db + e * 1024 + 128);
                            wgmma_ss(acc1, da + e * 4 + 2, dd + e * 1024);
                            wg_commit();
                            if (STAG && !first && e == STAGE && last) asm volatile("bar.arrive 2, 256;" ::: "memory");
                            if (!first || e) {
                                wg_wait<1>();
                                if (lane < 2) asm volatile("mbarrier.arrive.shared::cluster.b64 _, [%0];" ::"r"(e ? rel + 16 * xs : rel + 16 * xprev + 8) : "memory");
                            }
                        }
                        xprev = xs;
                        if (++xs == 3) { xs = 0; ph ^= 1; }
                    };
                    pair(true);
#pragma unroll 1
                    for (int kp = 1; kp < 10; kp++) {
                        if (STAG && kp == STAG && br == 0 && wg == 1) named_sync(2, 256);
                        last = kp == 9 && br == 0 && wg == 0;
                        pair(false);
                    }
                    wg_wait<0>();
                    pin(acc0); pin(acc1);
                    if (lane < 2) asm volatile("mbarrier.arrive.shared::cluster.b64 _, [%0];" ::"r"(rel + 16 * xprev + 8) : "memory");
                    TR(2 + 3 * br, threadIdx.x == 0);
                    const uint32_t wst = sb + (br == 0 ? OFF_R : 0) + warp * 768 + (lane & 7) * 16;
                    const uint32_t a0 = wst + (lane >> 3) * 128;
                    const uint32_t a1 = wst + (lane < 16 ? 512 + (lane >> 3) * 128 : 6144 + ((lane >> 3) - 2) * 128);
                    const uint32_t a2 = wst + 6144 + 256 + (lane >> 3) * 128;
                    const bool poly = (POLY16 >> ((mt * 8 + warp) & 15)) & 1;
                    const uint32_t augq = br ? 0u : (t & 1) ? 0x00003D2Du : 0x3F8043C0u;
                    const uint32_t augk = br ? 0u : (t & 1) ? (poly ? 0u : 0x00003F80u) : (poly ? 0x00003F80u : 0x3F800000u);
                    const uint32_t augv = (t & 1) ? 0u : 0x00003F80u;
                    const float sc2 = br ? 0.5f * QSCALE : QSCALE;
                    {
                        auto ACC = [&](int u, int j, int e) -> float& {
                            const int grp = !G ? 5 * u + j : (u & 1) ? (u >> 1) * 8 + 3 + j : j < 2 ? 24 + u + j : (u >> 1) * 8 + j - 2;
                            const int i = grp * 4 + e;
                            return i < N0 ? acc0[i % N0] : acc1[(i - N0 + 120 - N0) % (120 - N0)];
                        };
                        if (G ? ct == 6 : ct < 2) {
#pragma unroll
                            for (int i = 0; i < (G ? 80 : 120); i++) ACC(i / 20, i / 4 % 5, i % 4) *= i / 4 % 5 == 2 ? sc2 : QSCALE;
                        }
                        if (br == 1) named_sync(1, 256);
#pragma unroll
                        for (int u = 0; u < 6; u++) {
                            uint32_t v[2][5];
#pragma unroll
                            for (int j = 0; j < 10; j++) v[j / 5][j % 5] = pack2(ACC(u, j % 5, 2 * (j / 5)), ACC(u, j % 5, 2 * (j / 5) + 1));
                            const int blk = G ? (ct - 6) * 3 + (u >> 1) : ct;
                            const uint32_t aug = blk < 2 ? augq : blk < 4 ? augk : augv;
                            stsm4(a0 + u * 12288, v[0][0], v[0][1], t < 2 ? v[0][2] : aug, v[1][0]);
                            stsm4(a1 + u * 12288, v[1][1], t < 2 ? v[1][2] : aug, v[0][3], v[0][4]);
                            stsm4(a2 + u * 12288, t < 2 ? aug : v[0][2], v[1][3], v[1][4], t < 2 ? aug : v[1][2]);
                        }
                    }
                };
                if (ct < 6) tile(Bool<false>()); else tile(Bool<true>());
                fence_async_smem();
                __syncwarp();
                if (lane == 0) mbar_arrive(bars + (br ? B_STGA : wg ? B_STG1 : B_STGB));
                TR(3 + 3 * br, threadIdx.x == 0);
            }
            asm volatile("setmaxnreg.dec.sync.aligned.u32 128;");
        } else if (warp < 12) {
            asm volatile("setmaxnreg.dec.sync.aligned.u32 80;");
            if (warp != 9) {
                if (warp == 11) {
                    uint32_t xs = 0, ph = 0;
#pragma unroll
                    for (int i = 1; i < 3; i++) {
                        while (clock_lo() - t_start < (i == 1 ? G1 : G2)) {}
                        if (elect_one()) tma_x(sb + OFF_X + i * 16384, &tmX, i * 64, mt * 8, bars + B_FULL + 16 * i);
                    }
#pragma unroll 1
                    for (int P = 3; P < 20; P++) {
                        const int k0 = (P < 10 ? P : P - 13) * 64;
                        mbar_wait(bars + B_EMPTY + 16 * xs + 8, ph);
                        if (elect_one()) {
                            if (k0 >= 0) tma_x(sb + OFF_X + xs * 16384, &tmX, k0, mt * 8, bars + B_FULL + 16 * xs);
                            if (P == 7) { prefetch_tmap(&tmWa); prefetch_tmap(&tmGa); prefetch_tmap(&tmS); }
                        }
                        if (++xs == 3) { xs = 0; ph ^= 1; }
                    }
                } else {
                    const int at = (bid & 1) * 2 + (warp == 10);
                    WBox bx = w_box(&tmWb, &tmGb, nt, at);
                    uint32_t s = 0, ph = 0;
#pragma unroll
                    for (int i = 2; i < 6; i++) {
                        while (clock_lo() - t_start < (i < 4 ? G1 : G2)) {}
                        if (elect_one()) tma_3d_mc(sb + i * 16384 + at * 4096, bx.tm, bx.c0, i * 32, bx.c1, bars + B_FULL + 8 * i, 3);
                    }
#pragma unroll 1
                    for (int it = 6; it < 40; it++) {
                        const int k0 = (it < 20 ? it : it < 26 ? it - 6 : it - 26) * 32;
                        if (it == 20) bx = w_box(&tmWa, &tmGa, P1_NTA(nt), at);
                        const int bytes = ((s & 1) || (it >= 20 && it < 26)) ? 16384 : 32768;
                        mbar_wait(bars + B_EMPTY + 8 * s, ph);
                        if (elect_one()) {
                            tma_3d_mc(sb + s * 16384 + at * 4096, bx.tm, bx.c0, k0, bx.c1, bars + B_FULL + 8 * s, 3);
                            if (warp == 8) mbar_expect_tx(bars + B_FULL + 8 * s, bytes);
                        }
                        if (++s == 6) { s = 0; ph ^= 1; }
                    }
                }
                mbar_wait(bars + B_KV, 0);
                if (warp == 11) {
                    if (elect_one()) {
                        mbar_expect_tx(bars + B_KV + 8, 6 * 6144 + 2048);
                        load_kv(sb, h, 1, 4, 4, 0);
                        bulk_g2s(sb + OFF_G, g_gate + qb * 512, 2048, bars + B_KV + 8);
                        bulk_g2s(sb + OFF_R + 12288, g_qkv + (size_t)h * HEAD_BYTES + qb * 24576 + 12288, 12288, bars + B_KV + 8);
                    }
                } else {
                    mbar_wait(bars + B_EMPTY + 24, 0);
                    if (elect_one()) { if (warp == 8) load_kv(sb, h, 2, 8, 1, 12); else load_kv(sb, h, 2, 9, 11, 0); }
                }
            } else {
                mbar_wait(bars + B_STGB, 0);
                uint32_t tick = clock_lo() - PACE;
#pragma unroll 1
                for (int i = 0; i < 24; i++) {
                    const int hs = i < 12 ? i : i - 12, half = i < 12 ? 0 : 3072;
                    uint8_t* dst = g_qkv + (tile_slot(nt, hs) * (uint32_t)HEAD_BYTES + mt * 6144 + half);
                    if (i == 12) mbar_wait(bars + B_STG1, 0);
                    while (__shfl_sync(0xffffffffu, clock_lo() - tick, 0) < PACE) {}
                    tick += PACE;
                    if (elect_one()) bulk_s2g(dst, sb + OFF_R + hs * 6144 + half, 3072);
                }
                if (elect_one()) {
                    mbar_wait(bars + B_NRM, 0);
                    bulk_s2g(g_nrm + mt * 96 + nt * 12, bars + B_MISC, 48);
                    bulk_commit();
                    bulk_wait_all();
                    flag_add_done(g_flag + (F_QKVB + nt) * 32);
                    TR(8, true);
                    flag_wait_head(g_flag + F_QKVB * 32, h, 128);
                    fence_async_smem();
                    TR(9, true);
                    load_kv(sb, h, 0, 0, 4, 6);
                    bulk_g2s(sb + OFF_R, g_qkv + (size_t)h * HEAD_BYTES + qb * 24576, 12288, bars + B_KV);
                }
                __syncwarp();
                {
                    const uint32_t w = ldcg_u32(g_nrm + (lane < 16 ? lane * 96 + slot_index(32 + h) : (qb * 4 + (lane & 3)) * 96 + slot_index(h)));
                    const float kn = __uint_as_float(__reduce_max_sync(0xffffffffu, lane < 16 ? w : 0u));
                    if (lane >= 16 && lane < 20) s_misc[lane] = __uint_as_float(w) * kn <= SCORE_LIMIT2 ? 0.f : 1.f;
                    __syncwarp();
                    if (elect_one()) mbar_arrive(bars + B_KV + 24);
                }
            }
            __syncwarp();
            named_sync(5, 128);
            asm volatile("setmaxnreg.inc.sync.aligned.u32 128;");
        } else {
            mbar_wait(bars + B_FULL + 16, 0);
            {
                const uint8_t* wsrc = ((bid & 8) ? wob : woa) + (((bid & 7) * 40 + ((bid >> 4) & 1) * 320 + (lane & 7)) * 1280 + (bid >> 5) * 320);
                const uint2* gw = reinterpret_cast<const uint2*>(gate_w) + lane;
                const uint2* xr = reinterpret_cast<const uint2*>(x + (size_t)(bid * 16 + (warp - 12) * 4) * DM) + lane;
                uint2 gv[5];
#pragma unroll
                for (int i = 0; i < 5; i++) gv[i] = __ldg(gw + 32 * i);
#pragma unroll 1
                for (int e = 0; e < 4; e++) {
                    uint4 wv[2];
                    uint2 xv[5];
#pragma unroll
                    for (int c = 0; c < 2; c++) {
                        const uint32_t i = threadIdx.x - 384 + (e * 2 + c) * 128, kg = (i * 205u) >> 15;
                        if (i < 800) wv[c] = __ldg(reinterpret_cast<const uint4*>(wsrc + (kg * (10240 - 320) + (i >> 3) * 16)));
                    }
#pragma unroll
                    for (int i = 0; i < 5; i++) xv[i] = __ldg(xr + e * 160 + 32 * i);
                    float z = 0.f;
#pragma unroll
                    for (int i = 0; i < 5; i++) {
                        z = fmaf(bf_lo(xv[i].x), bf_lo(gv[i].x), z); z = fmaf(bf_hi(xv[i].x), bf_hi(gv[i].x), z);
                        z = fmaf(bf_lo(xv[i].y), bf_lo(gv[i].y), z); z = fmaf(bf_hi(xv[i].y), bf_hi(gv[i].y), z);
                    }
#pragma unroll
                    for (int o = 16; o; o >>= 1) z += __shfl_xor_sync(0xffffffffu, z, o);
                    if (lane == 0) g_gate[bid * 16 + (e & 1) * 8 + (warp - 12) * 2 + (e >> 1)] = __fdividef(1.f, 1.f + __expf(-z));
#pragma unroll
                    for (int c = 0; c < 2; c++) {
                        const uint32_t i = threadIdx.x - 384 + (e * 2 + c) * 128;
                        if (i < 800) stg128(g_wo + bid * 800 + i, wv[c]);
                    }
                }
                named_sync(6, 128);
                if (warp == 15 && elect_one()) { flag_add_done(g_flag + F_HELP * 32); TR2(53, true); }
                __syncwarp();
            }
            mbar_wait(bars + B_STGB, 0); mbar_wait(bars + B_STG1, 0);
#pragma unroll 1
            for (int hs = warp - 12; hs < 12; hs += 4) {
                uint32_t nm = 0;
                if (tile_slot(nt, hs) < 64) {
#pragma unroll 2
                    for (int i = 0; i < 4; i++) {
                        const uint32_t a = sb + OFF_R + hs * 6144 + (i * 4 + (lane >> 3)) * 384 + (lane & 7) * 16;
                        const uint4 k0 = lds128(a), k1 = lds128(a + 128);
                        uint32_t k2, k3;
                        asm volatile("ld.shared.v2.b32 {%0,%1}, [%2];" : "=r"(k2), "=r"(k3) : "r"(a + 256 + (hs & 1) * 8));
                        uint32_t n0 = hfma2(k2, k2, 0u), n1 = hfma2(k3, k3, 0u);
                        n0 = hfma2(k0.x, k0.x, n0); n1 = hfma2(k0.y, k0.y, n1); n0 = hfma2(k0.z, k0.z, n0); n1 = hfma2(k0.w, k0.w, n1);
                        n0 = hfma2(k1.x, k1.x, n0); n1 = hfma2(k1.y, k1.y, n1); n0 = hfma2(k1.z, k1.z, n0); n1 = hfma2(k1.w, k1.w, n1);
                        nm = max(nm, __float_as_uint((bf_lo(n0) + bf_hi(n0)) + (bf_lo(n1) + bf_hi(n1))));
                    }
                }
                nm = __reduce_max_sync(0xffffffffu, nm);
                if (lane == 0) s_misc[hs] = __uint_as_float(nm) * 1.03f;
            }
            fence_async_smem();
            __syncwarp();
            if (lane == 0) mbar_arrive(bars + B_NRM);
            TR2(27, threadIdx.x == 480);
        }
    }

    uint32_t aflag;
    {
        const uint64_t dK0 = mkdesc(sb, 128, 384, 0), dK1 = mkdesc(sb + 256, 0, 384, 0), dV = mkdesc(sb, 384, 128, 0);
        const int wid = fresh_wid();
        mbar_wait(bars + B_KV, 0);
        TR(10 + (threadIdx.x >> 7), (threadIdx.x & 127) == 0);
#pragma unroll 1
        for (int u = 0; u < 2; u++) {
            uint32_t q[8];
            {
                const uint32_t a = sb + OFF_R + (u * 32 + here(wid) * 2) * 384 + (fresh_tid() & 31) * 4;
                q[0] = lds32(a); q[1] = lds32(a + 384); q[2] = lds32(a + 128); q[3] = lds32(a + 512);
                q[4] = lds32(a + 256); q[5] = lds32(a + 640);
                q[6] = lds32(bars + B_ZERO); q[7] = lds32(bars + B_ZERO + 4);
            }
            float o[12];
#pragma unroll
            for (int i = 0; i < 12; i++) o[i] = 0.f;
            pin(o); pin(q);
            float s0[32], s1[32];
            uint32_t p[16];

            wg_fence(); qk_tile(s0, q, dK0 + (k_off(0) >> 4), dK1 + (k_off(0) >> 4)); wg_commit();
#pragma unroll
            for (int j = 0; j < 32; j += 2) {
                FENCE2(); qk_tile(s1, q, dK0 + (k_off(j + 1) >> 4), dK1 + (k_off(j + 1) >> 4)); wg_commit();
                wg_wait<1>(); pin(s0);
                exp_pv_tile(s0, p, o, dV + (v_off(j) >> 4), POLY16 >> (4 * (j & 3)));
                if (j == 2 || j == 6 || j == 18) { mbar_wait(bars + B_KV + (j == 2 ? 8 : j == 6 ? 16 : 24), 0); wg_fence(); }
                const bool ahead = j + 2 < 32 && j != LJ;
                if (ahead) { FENCE2(); qk_tile(s0, q, dK0 + (k_off(j + 2) >> 4), dK1 + (k_off(j + 2) >> 4)); wg_commit(); }
                {
                    TR(32 + u * 4 + j / 8, (j & 7) == 0 && fresh_tid() == 128);
                    if (j == 10) { if (u == 1 && elect_one()) mbar_arrive(bars + B_RET); }
                    if (j == SAJ) {
                        if (u == 0 && wid == 14 && elect_one()) {
                            const int bid = fresh_bid();
                            mbar_wait(bars + B_STGA, 0);
#pragma unroll
                            for (int i = 0; i < 3; i++) tma_store_3d(&tmS, sb + i * SLOT, 0, (P1_MP(bid) * 2 + (bid & 1)) * 16, 96 + tile_slot(P1_NTA(P1_NT(bid)), i * 4));
                            bulk_commit();
                        }
                        __syncwarp();
                    }
                    if (j == 12) {
                        if (u == 0 && wid == 14 && elect_one()) service(sb, 0, 0);
                        __syncwarp();
                    }
                    if (j == S1J) { if (u == 1 && wid == S1T && elect_one()) service(sb, 1, 0); __syncwarp(); }
                    if (j == 20 || j == 26) { if (u == 1 && elect_one()) mbar_arrive(bars + (j == 20 ? B_RET + 24 : B_R26)); }
                    if (j == S4J) { if (u == 1 && wid == S4T && elect_one()) service(sb, 4, 0); __syncwarp(); }
                    if (j == S3J) { if (u == 1 && wid == S3T && elect_one()) service(sb, 3, 0); __syncwarp(); }
                    if (j == 28) {
                        aflag = 0;
                        if (u == 1 && wid == 10) { aflag = ld_relaxed(atta_in(fresh_bid())); if (elect_one()) service(sb, 2, aflag); }
                        __syncwarp();
                    }
                }
                if (ahead) wg_wait<1>(); else wg_wait<0>();
                pin(s1);
                exp_pv_tile(s1, p, o, dV + (v_off(j + 1) >> 4), POLY16 >> (4 * ((j + 1) & 3)));
                if (j == LJ) {

                    wg_wait<0>();
                    if (u == 1) local_attn(sb, here(wid), dK0, dK1, dV);
                    wg_fence(); qk_tile(s0, q, dK0 + (k_off(j + 2) >> 4), dK1 + (k_off(j + 2) >> 4)); wg_commit();
                }
            }
            const int tid = fresh_tid(), lane = tid & 31, warp = here(wid);
            const int bid = fresh_bid(), h = bid >> 2, qb = bid & 3;
            const uint32_t gp = sb + OFF_G + (u * 256 + warp * 16 + (lane >> 2)) * 4;
            const float g0 = __uint_as_float(lds32(gp)), g1 = __uint_as_float(lds32(gp + 32));
            wg_wait<0>(); pin(o);
            TR(14 + u * 4 + (tid >> 7), (tid & 127) == 0);
            if (u == 1 && lane == 0) mbar_arrive(bars + B_RET + 16);
            float l0, l1;
            uint32_t w[6];
            finish_o(o, w, h & 1, 1.f - g0, 1.f - g1, lane, l0, l1);
            store_o(w, out_ptr(qb * 32 + u * 16 + warp, h, 80, lane), 0);
            const float sum = (((o[0] + o[1]) + (o[2] + o[3])) + ((o[4] + o[5]) + (o[6] + o[7]))) + ((o[8] + o[9]) + (o[10] + o[11]));
            if (__any_sync(0xffffffffu, !(fminf(l0, l1) >= 0x1p-30f && fmaxf(l0, l1) <= 0x1p100f && fabsf(sum) <= 1e37f && s_misc[16 + u * 2 + (warp >> 3)] == 0.f)))
                exact_rows(h, qb * 32 + u * 16 + warp, lane);
        }
        __syncwarp();
        if (elect_one()) mbar_arrive(bars + B_PUB + (wid >> 2) * 8);
    }

    {
        const int tid = fresh_tid(), lane = tid & 31;
        const int warp = __shfl_sync(0xffffffffu, tid >> 5, 0);
        const int bid = fresh_bid(), rank = bid & 1;
        if (warp >= 8) {
            asm volatile("setmaxnreg.dec.sync.aligned.u32 40;");
            if ((warp == 8 || warp == 12 || warp >= 14) && elect_one()) {
                const int wg = warp == 15 ? 0 : warp == 14 ? 1 : warp >> 2;
                mbar_wait(bars + B_PUB + 8 * wg, 0);
                TR2(48 + wg, true);
                flag_add_done(attb_out(bid, wg));
                TR2(wg == 0 ? 54 : wg == 1 ? 55 : wg == 2 ? 61 : 62, true);
            }
            if (warp == 13 && elect_one()) {
#pragma unroll
                for (int i = 0; i < 3; i++) { mbar_wait(bars + B_W0 + 8 * (i > WD ? i : WD), 0); load_wo(sb, 7 + i, 1); }
                TR2(57, true);
            }
            if (warp == 10 && elect_one()) {
                if (aflag < 16) flag_wait(atta_in(bid), 16);
                mbar_wait(bars + B_RET + 16, 0);
                if (aflag < 16) { load_frag(sb, bid, 0, 0); load_frag(sb, bid, 1, 0); }
                if (FD1) mbar_wait(bars + B_W0 + 8 * (FD1 - 1), 0);
                load_frag(sb, bid, 0, 1);
                mbar_wait(bars + B_W0 + 8 * (FD2 - 1), 0);
                fence_async_smem();
                load_frag(sb, bid, 0, 2);
                TR2(56, true);
            }
            if (warp == 11 && elect_one()) {
                mbar_wait(bars + B_AE, 0);
                fence_async_smem();
                flag_wait_fast(attb_in(bid), 16);
                TR2(52, true);
                load_frag(sb, bid, 1, 1); load_frag(sb, bid, 1, 2);
                if (atomicAdd(g_flag + F_EXIT * 32, 1u) == 127u) {
#pragma unroll 1
                    for (int i = 0; i < F_COUNT; i++) g_flag[i * 32] = 0u;
                }
            }
        } else {
            const int mh = warp >> 2;
            const int mt64 = (bid >> 5) * 8 + mh * 4 + ((bid >> 3) & 3);
            const int pos = frag_pos(warp & 3, lane);
            const uint2* ap = g_att + (mt64 * 160 + rank * 40) * 128 + pos;
            const uint32_t as0 = sb + frag_off(mh, 0) + pos * 8, as1 = sb + frag_off(mh, 5) + pos * 8, as9 = sb + frag_off(mh, 9) + pos * 8, fb = bars + B_AF + mh * 24;
            const uint64_t db = mkdesc(SB0, 2560, 128, 0);
            TR(22, tid == 0);
            uint32_t a[6][16];
            auto ldg = [&](int i) {
#pragma unroll
                for (int j = 0; j < 8; j++)
                    asm volatile("ld.global.L1::no_allocate.v2.b32 {%0, %1}, [%2];" : "=r"(a[i % 6][2 * j]), "=r"(a[i % 6][2 * j + 1])
                                 : "l"(ap + ((i / 5) * 80 + (i % 5) * 8 + j) * 128) : "memory");
            };
            auto lds = [&](int i) {
                if (i == 0 || i == 5 || i == 7) mbar_wait(fb + (i / 3) * 8, 0);
#pragma unroll
                for (int j = 0; j < 8; j++)
                    asm volatile("ld.shared.v2.b32 {%0, %1}, [%2];" : "=r"(a[i % 6][2 * j]), "=r"(a[i % 6][2 * j + 1])
                                 : "r"(i == 2 ? sb + frag2_off(mh, j >> 2) + pos * 8 + (j & 3) * 1024 : i == 9 ? as9 + j * 1024 : (i < 5 ? as0 : as1) + ((i % 5) * 8 + j) * 1024) : "memory");
            };
            float snd[40], keep[40];
            const uint64_t dk = db + rank * 80, ds = db + (rank ^ 1) * 80;
            TR(23, tid == 0);
            auto half = [&](float (&acc)[40], uint64_t d, int i) {
#pragma unroll
                for (int k = 0; k < 4; k++)
                    if (i + k == 0) wgmma_rs80f(acc, a[0][0], a[0][1], a[0][2], a[0][3], d + (wo_off(0) >> 4));
                    else wgmma_rs80(acc, a[i % 6][4 * k], a[i % 6][4 * k + 1], a[i % 6][4 * k + 2], a[i % 6][4 * k + 3], d + (wo_off(i) >> 4) + k * 320);
            };
            auto mma = [&](int i) {
                if (i == 0 || wo_bar(i) != wo_bar(i - 1)) mbar_wait(bars + B_WO + 8 * wo_bar(i), 0);
                pin(a[i % 6]);
                TR2(24, tid == 0 && i == 0);
                wg_fence();
                half(snd, ds, i);
                half(keep, dk, i);
                wg_commit();
            };
            lds(0); mma(0);
            wg_wait<0>();
            lds(1); mma(1);
            asm volatile("setmaxnreg.inc.sync.aligned.u32 216;");
            ldg(3); ldg(4);
            lds(2);
            __syncwarp();
            if (lane == 0) mbar_arrive(bars + B_AE);
#pragma unroll
            for (int i = 0; i < 3; i++) {
                wg_wait<1>();
                if (lane == 0) mbar_arrive(bars + B_W0 + 8 * i);
                mma(i + 2);
            }
            wg_wait<0>();
            if (lane == 0) mbar_arrive_cluster(bars + B_RET + 8, rank ^ 1);
            lds(5); lds(6);
            pin(a[5]); pin(a[0]);
            wg_fence(); half(snd, ds, 5); half(snd, ds, 6);
            half(keep, dk, 5);
            lds(7); lds(8); lds(9);
            pin(a[1]); pin(a[2]); pin(a[3]);
#pragma unroll
            for (int i = 7; i < 10; i++) { mbar_wait(bars + B_WO + 8 * wo_bar(i), 0); wg_fence(); half(snd, ds, i); }
            wg_commit();
#pragma unroll
            for (int i = 6; i < 10; i++) half(keep, dk, i);
            wg_commit();
            const uint32_t xs = sb + (mh ? wo_off(4) : wo_off(3)) + (tid & 127) * 16;
            {
                uint32_t ra, rb;
                asm volatile("mapa.shared::cluster.u32 %0, %1, %2;" : "=r"(ra) : "r"(xs), "r"(rank ^ 1));
                asm volatile("mapa.shared::cluster.u32 %0, %1, %2;" : "=r"(rb) : "r"(bars + B_XCH + 8 * mh), "r"(rank ^ 1));
                mbar_wait(bars + B_RET + 8, 0);
                wg_wait<1>();
                pin(snd);
                TR2(63, tid == 192);
#pragma unroll
                for (int j = 0; j < 5; j++)
                    asm volatile("st.async.weak.shared::cluster.mbarrier::complete_tx::bytes.v4.b32 [%0], {%1,%2,%3,%4}, [%5];"
                                 ::"r"(ra + j * 2048), "r"(pack2(snd[8 * j], snd[8 * j + 1])), "r"(pack2(snd[8 * j + 2], snd[8 * j + 3])),
                                   "r"(pack2(snd[8 * j + 4], snd[8 * j + 5])), "r"(pack2(snd[8 * j + 6], snd[8 * j + 7])), "r"(rb) : "memory");
            }
            named_sync(8 + mh, 128);
            mbar_wait(bars + B_XCH + 8 * mh, 0);
            TR2(58, tid == 192);
            uint4 rcv[10];
#pragma unroll
            for (int j = 0; j < 5; j++) {
                const uint4 v = lds128(xs + j * 2048);
                rcv[2 * j] = make_uint4(v.x << 16, v.x & 0xffff0000u, v.y << 16, v.y & 0xffff0000u);
                rcv[2 * j + 1] = make_uint4(v.z << 16, v.z & 0xffff0000u, v.w << 16, v.w & 0xffff0000u);
            }
            wg_wait<0>();
            pin(keep);
            TR2(25, tid == 0); TR2(60, tid == 192);
            uint32_t w[20];
#pragma unroll
            for (int j = 0; j < 10; j++) {
                const uint4 o = rcv[j];
                w[2 * j] = pack2(keep[4 * j] + __uint_as_float(o.x), keep[4 * j + 1] + __uint_as_float(o.y));
                w[2 * j + 1] = pack2(keep[4 * j + 2] + __uint_as_float(o.z), keep[4 * j + 3] + __uint_as_float(o.w));
            }
            const uint32_t ot = sb + frag_off(mh, 5) + (warp & 3) * 2816;
            const uint32_t sa = ot + (lane & 15) * 176 + (lane >> 4) * 16;
#pragma unroll
            for (int j = 0; j < 5; j++) stsm4(sa + j * 32, w[4 * j], w[4 * j + 1], w[4 * j + 2], w[4 * j + 3]);
            __syncwarp();
            __nv_bfloat16* ob = out + (size_t)(mt64 * 64 + (warp & 3) * 16) * DM + (bid & 7) * 80;
#pragma unroll
            for (int i = 0; i < 5; i++) {
                const int c = lane + 32 * i, r = c / 10;
                stg128(ob + ((r & 7) * 2 + (r >> 3)) * DM + (c % 10) * 8, lds128(ot + r * 176 + (c % 10) * 16));
            }
            TR2(26, tid == 0); TR2(59, tid == 192);
            TRFLUSH();
        }
    }
}

typedef CUresult (*EncodeFn)(CUtensorMap*, CUtensorMapDataType, cuuint32_t, void*, const cuuint64_t*, const cuuint64_t*,
                             const cuuint32_t*, const cuuint32_t*, CUtensorMapInterleave, CUtensorMapSwizzle,
                             CUtensorMapL2promotion, CUtensorMapFloatOOBfill);

void make_map(EncodeFn fn, CUtensorMap* tm, const void* ptr, int rank, const cuuint64_t* dims, const cuuint64_t* strides,
              const cuuint32_t* box, CUtensorMapSwizzle swz) {
    const cuuint32_t es[4] = {1, 1, 1, 1};
    fn(tm, CU_TENSOR_MAP_DATA_TYPE_BFLOAT16, rank, const_cast<void*>(ptr), dims, strides, box, es, CU_TENSOR_MAP_INTERLEAVE_NONE,
       swz, PROMO, CU_TENSOR_MAP_FLOAT_OOB_FILL_NONE);
}

}

extern "C" void kernel_launch(void* const* d_in, const int* in_sizes, int n_in, void* d_out, int out_size) {
    (void)in_sizes; (void)n_in; (void)out_size;
    const __nv_bfloat16* x = (const __nv_bfloat16*)d_in[0];
    const __nv_bfloat16* wqkv_a = (const __nv_bfloat16*)d_in[1];
    const __nv_bfloat16* wo_a = (const __nv_bfloat16*)d_in[2];
    const __nv_bfloat16* wqkv_b = (const __nv_bfloat16*)d_in[4];
    const __nv_bfloat16* wo_b = (const __nv_bfloat16*)d_in[5];
    const __nv_bfloat16* gate_w = (const __nv_bfloat16*)d_in[6];

    void* fnp = nullptr;
    cudaDriverEntryPointQueryResult qr;
    cudaGetDriverEntryPoint("cuTensorMapEncodeTiled", &fnp, cudaEnableDefault, &qr);
    EncodeFn enc = (EncodeFn)fnp;
    void* qkv = nullptr;
    cudaGetSymbolAddress(&qkv, g_qkv);

    CUtensorMap tmX, tmWb, tmWa, tmGb, tmGa, tmS;
    {
        const cuuint64_t d[4] = {640, 8, 2, 128}, s[3] = {2560, 1280, 20480};
        const cuuint32_t b[4] = {64, 8, 2, 8};
        make_map(enc, &tmX, x, 4, d, s, b, CU_TENSOR_MAP_SWIZZLE_128B);
    }
    {
        const cuuint64_t d[3] = {320, 640, 6}, dg[3] = {16, 640, 6}, s[2] = {3840, 640};
        const cuuint32_t b[3] = {64, 32, 1}, bg[3] = {16, 32, 4};
        make_map(enc, &tmWb, wqkv_b, 3, d, s, b, CU_TENSOR_MAP_SWIZZLE_128B);
        make_map(enc, &tmWa, wqkv_a, 3, d, s, b, CU_TENSOR_MAP_SWIZZLE_128B);
        make_map(enc, &tmGb, wqkv_b + 240, 3, dg, s, bg, CU_TENSOR_MAP_SWIZZLE_32B);
        make_map(enc, &tmGa, wqkv_a + 240, 3, dg, s, bg, CU_TENSOR_MAP_SWIZZLE_32B);
    }
    {
        const cuuint64_t d[3] = {192, 256, 192}, s[2] = {384, (cuuint64_t)HEAD_BYTES};
        const cuuint32_t b[3] = {192, 16, 4};
        make_map(enc, &tmS, qkv, 3, d, s, b, CU_TENSOR_MAP_SWIZZLE_NONE);
    }
    cudaFuncSetAttribute(k_fused, cudaFuncAttributeMaxDynamicSharedMemorySize, SMEM_BYTES);
    k_fused<<<128, 512, SMEM_BYTES, cudaStreamPerThread>>>(tmX, tmWb, tmWa, tmGb, tmGa, tmS, x, gate_w, (const uint8_t*)wqkv_b,
                                                          (const uint8_t*)wo_a, (const uint8_t*)wo_b, (__nv_bfloat16*)d_out);
}
```
